```python
import torch

def _softmax(x, axis=-1):
    return torch.softmax(x, dim=axis)
def _gelu(x):
    return torch.nn.functional.gelu(x, approximate="tanh")
def _silu(x):
    return torch.nn.functional.silu(x)
def _sigmoid(x):
    return torch.sigmoid(x)
def _layernorm(x, axis=-1, eps=1e-5):
    m = x.mean(dim=axis, keepdim=True)
    v = x.var(dim=axis, keepdim=True, unbiased=False)
    return (x - m) / torch.sqrt(v + eps)
def _scatter_add(tgt, idx, src, axis=0):
    return tgt.clone().index_add_(axis, idx, src)
def _segment_sum(src, seg, n):
    out = torch.zeros((n,) + src.shape[1:], dtype=src.dtype)
    return out.index_add_(0, seg, src)
def _pad(x, pw):
    flat = tuple(v for pair in reversed(pw) for v in pair)
    return torch.nn.functional.pad(x, flat)

kernel_name = 'recurrent_scan__sliding_block_cached__glu_gated_swiglu__prompt'

def setup_inputs():

    _w = (lambda a: (lambda t: t.to(torch.bfloat16) if t.is_floating_point() else t)(torch.as_tensor(a)))
    def _A_setup():
        B, Sq, D = 1, 2048, 640
        Hq, Hkv, Sk, Dh = 32, 32, 2048, 128
        assert Hq % Hkv == 0, (Hq, Hkv)
        return {
            "x": _w((lambda *s: torch.randn(*s, dtype=torch.bfloat16) * 0.05)(B, Sq, D)),
            "k_cache": _w((lambda *s: torch.randn(*s, dtype=torch.bfloat16) * 1.6)(B, Hkv, Sk, Dh)),
            "v_cache": _w((lambda *s: torch.randn(*s, dtype=torch.bfloat16) * 1.6)(B, Hkv, Sk, Dh)),
            "wq": _w((lambda *s: torch.randn(*s, dtype=torch.bfloat16) * 1.6)(D, Hq * Dh) * (D ** -0.5)),
            "wo": _w((lambda *s: torch.randn(*s, dtype=torch.bfloat16) * 1.6)(Hq * Dh, D) * ((Hq * Dh) ** -0.5)),
        }
    _A_in = _A_setup()

    def _B_setup():
        B, S, D, F = 1, 2048, 640, 1728
        return {
            "x": _w((lambda *s: torch.randn(*s, dtype=torch.bfloat16) * 0.05)(B, S, D)),
            "w1": _w((lambda *s: torch.randn(*s, dtype=torch.bfloat16) * 0.2)(D, F) * (2.0 / D) ** 0.5),
            "w3": _w((lambda *s: torch.randn(*s, dtype=torch.bfloat16) * 0.2)(D, F) * (2.0 / D) ** 0.5),
            "w2": _w((lambda *s: torch.randn(*s, dtype=torch.bfloat16) * 0.2)(F, D) * (2.0 / F) ** 0.5),
        }
    _B_in = _B_setup()

    return {
        "A_x": _A_in["x"],
        "A_k_cache": _A_in["k_cache"],
        "A_v_cache": _A_in["v_cache"],
        "A_wq": _A_in["wq"],
        "A_wo": _A_in["wo"],
        "B_x": _B_in["x"],
        "B_w1": _B_in["w1"],
        "B_w3": _B_in["w3"],
        "B_w2": _B_in["w2"],
    }

def reference(A_x, A_k_cache, A_v_cache, A_wq, A_wo, B_x, B_w1, B_w3, B_w2):
    def _A_ref(x, k_cache, v_cache, wq, wo):
        B, Sq, D = x.shape
        Hq, Dh = 32, 128
        Hkv, Sk = k_cache.shape[1], k_cache.shape[2]
        W = min(4096, max(256, Sk // 4))
        rep = Hq // Hkv
        q = (lambda x, *d: x.permute(*d))((x @ wq).reshape(B, Sq, Hq, Dh), 0, 2, 1, 3)
        k = (lambda x, n, axis: torch.repeat_interleave(x, n, dim=axis))(k_cache[:, :, Sk - W:, :], rep, axis=1)
        v = (lambda x, n, axis: torch.repeat_interleave(x, n, dim=axis))(v_cache[:, :, Sk - W:, :], rep, axis=1)
        scores = torch.einsum("bhqd,bhkd->bhqk", q, k) * (Dh ** -0.5)
        p = _softmax(scores, axis=-1)
        o = torch.einsum("bhqk,bhkd->bhqd", p, v)
        return (lambda x, *d: x.permute(*d))(o, 0, 2, 1, 3).reshape(B, Sq, Hq * Dh) @ wo

    def _B_ref(x, w1, w3, w2):
        gate = torch.einsum("bsd,df->bsf", x, w1)
        up = torch.einsum("bsd,df->bsf", x, w3)
        h = _silu(gate) * up
        out = torch.einsum("bsf,fd->bsd", h, w2)
        return out

    x = A_x
    xn = _layernorm(x, axis=-1)
    s = _A_ref(xn, A_k_cache, A_v_cache, A_wq, A_wo)
    g = _silu(_B_ref(xn, B_w1, B_w3, B_w2))
    return x + s * g
```

```cpp
#include <cuda_runtime.h>
#include <cuda_bf16.h>
#include <cuda.h>
#include <stdint.h>
#include <stdio.h>

#define PINGPONG
#define PUB_RELAXED
#define NO_PREFETCH

namespace {

constexpr int S_LEN = 2048, DM = 640, NH = 32, DH = 128, SKV = 2048, WIN = 512, KOFF = SKV - WIN, FF = 1728;
constexpr int SLOT = 16384;
constexpr int OFF_RINGG = 10 * SLOT;
constexpr int OFF_BAR = 14 * SLOT;
constexpr int SMEM_BYTES = OFF_BAR + 1024 + 1024;
constexpr int ST3 = 57344;

constexpr int NP = 5;
enum { B_FULLG = 0, B_EMPTYG = 4, B_FULLA = 8, B_EMPTYA = 15, B_FULL3 = 22, B_EMPTY3 = 26, B_XNFREE = 30, B_PUB = 31, B_IN = 39, B_X = 42, B_XS = 52, B_COUNT = 53 };

__device__ __align__(1024) __nv_bfloat16 g_oq[S_LEN * NH * DH];
__device__ __align__(1024) __nv_bfloat16 g_h[S_LEN * FF];
__device__ __align__(1024) uint4 g_part[32 * 4 * 4 * 5 * 256];
__device__ __align__(1024) unsigned g_cnt[16 * 128];

__constant__ uint8_t c_blk[8][28] = {
    { 0,  1,  8,  9, 16,  2,  3, 10, 11, 18,  4,  5, 12, 13, 20,  6,  7, 14, 15, 22, 23,  0,  0,  0,  0,  0,  0,  0},
    { 0,  1,  8,  9, 16,  2,  3, 10, 11, 18,  4,  5, 12, 13, 20,  6,  7, 14, 15, 22,  0,  0,  0,  0,  0,  0,  0,  0},
    {17, 24, 25, 32, 33, 19, 26, 27, 34, 35, 21, 28, 29, 36, 37, 44, 30, 31, 38, 39, 46,  0,  0,  0,  0,  0,  0,  0},
    {17, 24, 25, 32, 33, 19, 26, 27, 34, 35, 21, 28, 29, 36, 37, 23, 30, 31, 38, 39,  0,  0,  0,  0,  0,  0,  0,  0},
    {40, 41, 48, 49, 56, 57, 42, 43, 50, 51, 58, 59, 45, 52, 53, 60, 61, 47, 54, 55, 62, 63,  0,  0,  0,  0,  0,  0},
    {40, 41, 48, 49, 56, 57, 42, 43, 50, 51, 58, 59, 44, 45, 52, 53, 60, 61, 46, 47, 54, 55, 62, 63,  0,  0,  0,  0},
    { 0,  1,  2,  3,  4,  5,  6,  7,  8,  9, 10, 11, 12, 13, 14, 15, 16, 17, 18, 19, 20, 21, 22, 23, 24, 25, 26,  0},
    { 0,  1,  2,  3,  4,  5,  6,  7,  8,  9, 10, 11, 12, 13, 14, 15, 16, 17, 18, 19, 20, 21, 22, 23, 24, 25, 26,  0},
};

__device__ __forceinline__ uint32_t smem_u32(const void* p) { return (uint32_t)__cvta_generic_to_shared(p); }
__device__ __forceinline__ void mbar_init(uint32_t bar, uint32_t count) {
    asm volatile("mbarrier.init.shared::cta.b64 [%0], %1;" :: "r"(bar), "r"(count));
}
__device__ __forceinline__ void mbar_expect_tx(uint32_t bar, uint32_t bytes) {
    asm volatile("mbarrier.arrive.expect_tx.shared::cta.b64 _, [%0], %1;" :: "r"(bar), "r"(bytes) : "memory");
}
__device__ __forceinline__ void mbar_arrive(uint32_t bar) {
    asm volatile("mbarrier.arrive.shared::cta.b64 _, [%0];" :: "r"(bar) : "memory");
}
__device__ __forceinline__ void mbar_arrive_cluster(uint32_t bar, uint32_t cta) {
    asm volatile("{\n.reg .b32 ra;\nmapa.shared::cluster.u32 ra, %0, %1;\nmbarrier.arrive.shared::cluster.b64 _, [ra];\n}"
                 :: "r"(bar), "r"(cta) : "memory");
}
__device__ __forceinline__ void mbar_wait(uint32_t bar, uint32_t parity, int code = 0) {
    (void)code;
    asm volatile("{\n.reg .pred p, q;\n.reg .u64 t0, t1;\n"
                 "mbarrier.try_wait.parity.shared::cta.b64 p, [%0], %1;\n"
                 "@p bra DONE;\n"
                 "mov.u64 t0, %%clock64;\n"
                 "LOOP:\n"
                 "mbarrier.try_wait.parity.shared::cta.b64 p, [%0], %1;\n"
                 "@p bra DONE;\n"
                 "mov.u64 t1, %%clock64;\n"
                 "sub.u64 t1, t1, t0;\n"
                 "setp.lt.u64 q, t1, 4000000000;\n"
                 "@q bra LOOP;\n"
                 "trap;\n"
                 "DONE:\n}"
                 :: "r"(bar), "r"(parity) : "memory");
}
__device__ __forceinline__ void mbar_wait_u(uint32_t bar, uint32_t parity) {
    asm volatile("{\n.reg .pred p, q;\n.reg .u64 t0, t1;\n"
                 "mbarrier.try_wait.parity.shared::cta.b64 p, [%0], %1;\n"
                 "vote.sync.all.pred p, p, 0xffffffff;\n"
                 "@p bra.uni DONE;\n"
                 "mov.u64 t0, %%clock64;\n"
                 "LOOP:\n"
                 "mbarrier.try_wait.parity.shared::cta.b64 p, [%0], %1;\n"
                 "vote.sync.all.pred p, p, 0xffffffff;\n"
                 "@p bra.uni DONE;\n"
                 "mov.u64 t1, %%clock64;\n"
                 "sub.u64 t1, t1, t0;\n"
                 "setp.lt.u64 q, t1, 4000000000;\n"
                 "vote.sync.any.pred q, q, 0xffffffff;\n"
                 "@q bra.uni LOOP;\n"
                 "trap;\n"
                 "DONE:\n}"
                 :: "r"(bar), "r"(parity) : "memory");
}
__device__ __forceinline__ void mbar_wait2(uint32_t b0, uint32_t p0, uint32_t b1, uint32_t p1) {
    asm volatile("{\n.reg .pred p, q;\n.reg .u64 t0, t1;\n"
                 "mbarrier.try_wait.parity.shared::cta.b64 p, [%0], %1;\n"
                 "mbarrier.try_wait.parity.shared::cta.b64 q, [%2], %3;\n"
                 "and.pred p, p, q;\n"
                 "vote.sync.all.pred p, p, 0xffffffff;\n"
                 "@p bra.uni DONE;\n"
                 "mov.u64 t0, %%clock64;\n"
                 "LOOP:\n"
                 "mbarrier.try_wait.parity.shared::cta.b64 p, [%0], %1;\n"
                 "mbarrier.try_wait.parity.shared::cta.b64 q, [%2], %3;\n"
                 "and.pred p, p, q;\n"
                 "vote.sync.all.pred p, p, 0xffffffff;\n"
                 "@p bra.uni DONE;\n"
                 "mov.u64 t1, %%clock64;\n"
                 "sub.u64 t1, t1, t0;\n"
                 "setp.lt.u64 q, t1, 4000000000;\n"
                 "vote.sync.any.pred q, q, 0xffffffff;\n"
                 "@q bra.uni LOOP;\n"
                 "trap;\n"
                 "DONE:\n}"
                 :: "r"(b0), "r"(p0), "r"(b1), "r"(p1) : "memory");
}
__device__ __forceinline__ uint32_t mbar_probe(uint32_t b0, uint32_t p0) {
    uint32_t ok;
    asm volatile("{\n.reg .pred p;\nmbarrier.test_wait.parity.shared::cta.b64 p, [%1], %2;\nselp.u32 %0, 1, 0, p;\n}"
                 : "=r"(ok) : "r"(b0), "r"(p0) : "memory");
    return ok;
}
__device__ __forceinline__ void mbar_wait4(uint32_t b0, uint32_t p0, uint32_t b1, uint32_t p1, uint32_t b2, uint32_t p2, uint32_t b3, uint32_t p3) {
    asm volatile("{\n.reg .pred p, q, r, s;\n.reg .u64 t0, t1;\n"
                 "mov.u64 t0, 0;\n"
                 "LOOP:\n"
                 "mbarrier.try_wait.parity.shared::cta.b64 p, [%0], %1;\n"
                 "mbarrier.try_wait.parity.shared::cta.b64 q, [%2], %3;\n"
                 "mbarrier.try_wait.parity.shared::cta.b64 r, [%4], %5;\n"
                 "mbarrier.try_wait.parity.shared::cta.b64 s, [%6], %7;\n"
                 "and.pred p, p, q;\nand.pred r, r, s;\nand.pred p, p, r;\n"
                 "vote.sync.all.pred p, p, 0xffffffff;\n"
                 "@p bra.uni DONE;\n"
                 "mov.u64 t1, %%clock64;\n"
                 "setp.eq.u64 q, t0, 0;\n"
                 "selp.u64 t0, t1, t0, q;\n"
                 "sub.u64 t1, t1, t0;\n"
                 "setp.lt.u64 q, t1, 4000000000;\n"
                 "vote.sync.any.pred q, q, 0xffffffff;\n"
                 "@q bra.uni LOOP;\n"
                 "trap;\n"
                 "DONE:\n}"
                 :: "r"(b0), "r"(p0), "r"(b1), "r"(p1), "r"(b2), "r"(p2), "r"(b3), "r"(p3) : "memory");
}
__device__ __forceinline__ uint32_t mbar_probe2(uint32_t b0, uint32_t p0, uint32_t b1, uint32_t p1) {
    uint32_t ok;
    asm volatile("{\n.reg .pred p, q;\n"
                 "mbarrier.test_wait.parity.shared::cta.b64 p, [%1], %2;\n"
                 "mbarrier.test_wait.parity.shared::cta.b64 q, [%3], %4;\n"
                 "and.pred p, p, q;\n"
                 "selp.u32 %0, 1, 0, p;\n}"
                 : "=r"(ok) : "r"(b0), "r"(p0), "r"(b1), "r"(p1) : "memory");
    return ok;
}
__device__ __forceinline__ uint32_t mapa_u32(uint32_t addr, uint32_t cta) {
    uint32_t r;
    asm("mapa.shared::cluster.u32 %0, %1, %2;" : "=r"(r) : "r"(addr), "r"(cta));
    return r;
}
__device__ __forceinline__ void mbar_arrive_remote(uint32_t cluster_addr) {
    asm volatile("mbarrier.arrive.shared::cluster.b64 _, [%0];" :: "r"(cluster_addr) : "memory");
}
__device__ __forceinline__ void mbar_arrive_remote_if(uint32_t cluster_addr, uint32_t flag) {
    asm volatile("{\n.reg .pred p;\nsetp.ne.u32 p, %1, 0;\n@p mbarrier.arrive.shared::cluster.b64 _, [%0];\n}"
                 :: "r"(cluster_addr), "r"(flag) : "memory");
}
__device__ __forceinline__ void mbar_arrive_if(uint32_t addr, uint32_t flag) {
    asm volatile("{\n.reg .pred p;\nsetp.ne.u32 p, %1, 0;\n@p mbarrier.arrive.shared::cta.b64 _, [%0];\n}"
                 :: "r"(addr), "r"(flag) : "memory");
}
__device__ __forceinline__ void mbar_arrive_warp(uint32_t addr, uint32_t lane_flag) {
    __syncwarp();
    asm volatile("{\n.reg .pred p;\nsetp.ne.u32 p, %1, 0;\n@p mbarrier.arrive.shared::cta.b64 _, [%0];\n}"
                 :: "r"(addr), "r"(lane_flag) : "memory");
}
__device__ __forceinline__ void tma_2d_mc(uint32_t dst, const CUtensorMap* m, int c0, int c1, uint32_t bar) {
    asm volatile("cp.async.bulk.tensor.2d.shared::cluster.global.mbarrier::complete_tx::bytes.multicast::cluster"
                 " [%0], [%1, {%3, %4}], [%2], %5;"
                 :: "r"(dst), "l"(m), "r"(bar), "r"(c0), "r"(c1), "h"((uint16_t)3) : "memory");
}
__device__ __forceinline__ void tma_2d(uint32_t dst, const CUtensorMap* m, int c0, int c1, uint32_t bar) {
    asm volatile("cp.async.bulk.tensor.2d.shared::cluster.global.mbarrier::complete_tx::bytes [%0], [%1, {%3, %4}], [%2];"
                 :: "r"(dst), "l"(m), "r"(bar), "r"(c0), "r"(c1) : "memory");
}
__device__ __forceinline__ void tma_5d_mc(uint32_t dst, const CUtensorMap* m, int c2, int c4, uint32_t bar) {
    asm volatile("cp.async.bulk.tensor.5d.shared::cluster.global.mbarrier::complete_tx::bytes.multicast::cluster"
                 " [%0], [%1, {%5, %5, %3, %5, %4}], [%2], %6;"
                 :: "r"(dst), "l"(m), "r"(bar), "r"(c2), "r"(c4), "r"(0), "h"((uint16_t)3) : "memory");
}
__device__ __forceinline__ void bulk_load(uint32_t dst, const void* src, uint32_t bytes, uint32_t bar) {
    asm volatile("cp.async.bulk.shared::cluster.global.mbarrier::complete_tx::bytes [%0], [%1], %2, [%3];"
                 :: "r"(dst), "l"(src), "r"(bytes), "r"(bar) : "memory");
}
__device__ __forceinline__ void bulk_store(void* dst, uint32_t src, uint32_t bytes) {
    asm volatile("cp.async.bulk.global.shared::cta.bulk_group [%0], [%1], %2;" :: "l"(dst), "r"(src), "r"(bytes) : "memory");
    asm volatile("cp.async.bulk.commit_group;" ::: "memory");
}
template <int N> __device__ __forceinline__ void bulk_wait() { asm volatile("cp.async.bulk.wait_group %0;" :: "n"(N) : "memory"); }
__device__ __forceinline__ void prefetch_2d(const CUtensorMap* m, int c0, int c1) {
    asm volatile("cp.async.bulk.prefetch.tensor.2d.L2.global [%0, {%1, %2}];" :: "l"(m), "r"(c0), "r"(c1) : "memory");
}
__device__ __forceinline__ void prefetch_5d(const CUtensorMap* m, int c2, int c4) {
    asm volatile("cp.async.bulk.prefetch.tensor.5d.L2.global [%0, {%3, %3, %1, %3, %2}];" :: "l"(m), "r"(c2), "r"(c4), "r"(0) : "memory");
}
__device__ __forceinline__ void cluster_sync() {
    asm volatile("barrier.cluster.arrive.release.aligned;\nbarrier.cluster.wait.acquire.aligned;" ::: "memory");
}
__device__ __forceinline__ void prefetch_tmap(const CUtensorMap* m) { asm volatile("prefetch.tensormap [%0];" :: "l"(m) : "memory"); }
__device__ __forceinline__ void cluster_arrive_relaxed() { asm volatile("barrier.cluster.arrive.relaxed.aligned;" ::: "memory"); }
__device__ __forceinline__ void cluster_wait() { asm volatile("barrier.cluster.wait.acquire.aligned;" ::: "memory"); }
__device__ __forceinline__ void mma_bf16(float (&d)[4], uint32_t a0, uint32_t a1, uint32_t a2, uint32_t a3, uint32_t b0, uint32_t b1) {
    asm volatile("mma.sync.aligned.m16n8k16.row.col.f32.bf16.bf16.f32 {%0, %1, %2, %3}, {%4, %5, %6, %7}, {%8, %9}, {%0, %1, %2, %3};"
                 : "+f"(d[0]), "+f"(d[1]), "+f"(d[2]), "+f"(d[3]) : "r"(a0), "r"(a1), "r"(a2), "r"(a3), "r"(b0), "r"(b1));
}
__device__ __forceinline__ uint32_t hsub2_bf16(uint32_t a, uint32_t b) { uint32_t r; asm("sub.rn.bf16x2 %0, %1, %2;" : "=r"(r) : "r"(a), "r"(b)); return r; }
__device__ __forceinline__ uint32_t hfma2_bf16(uint32_t a, uint32_t b, uint32_t c) { uint32_t r; asm("fma.rn.bf16x2 %0, %1, %2, %3;" : "=r"(r) : "r"(a), "r"(b), "r"(c)); return r; }
__device__ __forceinline__ uint32_t cluster_ctarank() { uint32_t r; asm volatile("mov.u32 %0, %%cluster_ctarank;" : "=r"(r)); return r; }
__device__ __forceinline__ void wgmma_fence() { asm volatile("wgmma.fence.sync.aligned;" ::: "memory"); }
__device__ __forceinline__ void wgmma_commit() { asm volatile("wgmma.commit_group.sync.aligned;" ::: "memory"); }
template <int N> __device__ __forceinline__ void wgmma_wait() { asm volatile("wgmma.wait_group.sync.aligned %0;" :: "n"(N) : "memory"); }
template <int N> __device__ __forceinline__ void fence_regs(float (&d)[N]) {
#pragma unroll
    for (int i = 0; i < N; i++) asm volatile("" : "+f"(d[i]) :: "memory");
}
template <int N> __device__ __forceinline__ void fence_regs(uint32_t (&d)[N]) {
#pragma unroll
    for (int i = 0; i < N; i++) asm volatile("" : "+r"(d[i]) :: "memory");
}
__device__ __forceinline__ void named_sync(int id, int n) { asm volatile("bar.sync %0, %1;" :: "r"(id), "r"(n) : "memory"); }
__device__ __forceinline__ void named_arrive(int id, int n) { asm volatile("bar.arrive %0, %1;" :: "r"(id), "r"(n) : "memory"); }
__device__ __forceinline__ uint32_t desc_lo(uint32_t addr, uint32_t lbo_bytes) {
    return ((addr & 0x3FFFF) >> 4) | ((lbo_bytes >> 4) << 16);
}
__device__ __forceinline__ uint32_t opaque(uint32_t v) { asm volatile("" : "+r"(v)); return v; }
__device__ __forceinline__ uint32_t pack_bf16(float lo, float hi) {
    uint32_t r;
    asm("cvt.rn.bf16x2.f32 %0, %1, %2;" : "=r"(r) : "f"(hi), "f"(lo));
    return r;
}
__device__ __forceinline__ float bf_lo(uint32_t v) { return __uint_as_float(v << 16); }
__device__ __forceinline__ float bf_hi(uint32_t v) { return __uint_as_float(v & 0xffff0000u); }
__device__ __forceinline__ float bf_round(float x) { return bf_lo(pack_bf16(x, 0.f)); }
__device__ __forceinline__ float ex2(float x) { float r; asm("ex2.approx.ftz.f32 %0, %1;" : "=f"(r) : "f"(x)); return r; }
__device__ __forceinline__ float rcp(float x) { float r; asm("rcp.approx.ftz.f32 %0, %1;" : "=f"(r) : "f"(x)); return r; }
__device__ __forceinline__ float silu_f(float x) { return x * rcp(1.0f + ex2(x * -1.4426950408889634f)); }
__device__ __forceinline__ uint32_t hmul2_bf16(uint32_t a, uint32_t b) {
    uint32_t r;
    asm("mul.rn.bf16x2 %0, %1, %2;" : "=r"(r) : "r"(a), "r"(b));
    return r;
}
__device__ __forceinline__ unsigned ld_acquire(const unsigned* p) {
    unsigned v;
    asm volatile("ld.acquire.gpu.global.u32 %0, [%1];" : "=r"(v) : "l"(p) : "memory");
    return v;
}
__device__ __forceinline__ void red_release(unsigned* p, unsigned v) {
    asm volatile("red.release.gpu.global.add.u32 [%0], %1;" :: "l"(p), "r"(v) : "memory");
}
__device__ __forceinline__ void wait_flag(const unsigned* p, unsigned target, int code) {
    (void)code;
    if ((int)(ld_acquire(p) - target) >= 0) return;
    long long t0 = clock64();
    while ((int)(ld_acquire(p) - target) < 0) {
        __nanosleep(40);
        if (clock64() - t0 > 4000000000ll) __trap();
    }
}

__device__ __forceinline__ void wgmma_ss_n128_tb(float (&d)[64], uint32_t da, uint32_t db, int scale_d) {
    asm volatile("{\n.reg .pred p;\n.reg .b64 da, db;\nsetp.ne.b32 p, %66, 0;\n"
        "mov.b64 da, {%64, 0x40000040};\nmov.b64 db, {%65, 0x40000040};\n"
        "wgmma.mma_async.sync.aligned.m64n128k16.f32.bf16.bf16 "
        "{%0, %1, %2, %3, %4, %5, %6, %7, %8, %9, %10, %11, %12, %13, %14, %15, "
        "%16, %17, %18, %19, %20, %21, %22, %23, %24, %25, %26, %27, %28, %29, %30, %31, "
        "%32, %33, %34, %35, %36, %37, %38, %39, %40, %41, %42, %43, %44, %45, %46, %47, "
        "%48, %49, %50, %51, %52, %53, %54, %55, %56, %57, %58, %59, %60, %61, %62, %63}, "
        "da, db, p, 1, 1, 0, 1;\n}"
        : "+f"(d[0]), "+f"(d[1]), "+f"(d[2]), "+f"(d[3]), "+f"(d[4]), "+f"(d[5]), "+f"(d[6]), "+f"(d[7]),
          "+f"(d[8]), "+f"(d[9]), "+f"(d[10]), "+f"(d[11]), "+f"(d[12]), "+f"(d[13]), "+f"(d[14]), "+f"(d[15]),
          "+f"(d[16]), "+f"(d[17]), "+f"(d[18]), "+f"(d[19]), "+f"(d[20]), "+f"(d[21]), "+f"(d[22]), "+f"(d[23]),
          "+f"(d[24]), "+f"(d[25]), "+f"(d[26]), "+f"(d[27]), "+f"(d[28]), "+f"(d[29]), "+f"(d[30]), "+f"(d[31]),
          "+f"(d[32]), "+f"(d[33]), "+f"(d[34]), "+f"(d[35]), "+f"(d[36]), "+f"(d[37]), "+f"(d[38]), "+f"(d[39]),
          "+f"(d[40]), "+f"(d[41]), "+f"(d[42]), "+f"(d[43]), "+f"(d[44]), "+f"(d[45]), "+f"(d[46]), "+f"(d[47]),
          "+f"(d[48]), "+f"(d[49]), "+f"(d[50]), "+f"(d[51]), "+f"(d[52]), "+f"(d[53]), "+f"(d[54]), "+f"(d[55]),
          "+f"(d[56]), "+f"(d[57]), "+f"(d[58]), "+f"(d[59]), "+f"(d[60]), "+f"(d[61]), "+f"(d[62]), "+f"(d[63])
        : "r"(da), "r"(db), "r"(scale_d));
}
__device__ __forceinline__ void wgmma_rs_n128_kb(float (&d)[64], uint32_t a0, uint32_t a1, uint32_t a2, uint32_t a3, uint32_t db, int scale_d) {
    asm volatile("{\n.reg .pred p;\n.reg .b64 da, db;\nsetp.ne.b32 p, %69, 0;\n"
        "mov.b64 db, {%68, 0x40000040};\n"
        "wgmma.mma_async.sync.aligned.m64n128k16.f32.bf16.bf16 "
        "{%0, %1, %2, %3, %4, %5, %6, %7, %8, %9, %10, %11, %12, %13, %14, %15, "
        "%16, %17, %18, %19, %20, %21, %22, %23, %24, %25, %26, %27, %28, %29, %30, %31, "
        "%32, %33, %34, %35, %36, %37, %38, %39, %40, %41, %42, %43, %44, %45, %46, %47, "
        "%48, %49, %50, %51, %52, %53, %54, %55, %56, %57, %58, %59, %60, %61, %62, %63}, "
        "{%64, %65, %66, %67}, db, p, 1, 1, 0;\n}"
        : "+f"(d[0]), "+f"(d[1]), "+f"(d[2]), "+f"(d[3]), "+f"(d[4]), "+f"(d[5]), "+f"(d[6]), "+f"(d[7]),
          "+f"(d[8]), "+f"(d[9]), "+f"(d[10]), "+f"(d[11]), "+f"(d[12]), "+f"(d[13]), "+f"(d[14]), "+f"(d[15]),
          "+f"(d[16]), "+f"(d[17]), "+f"(d[18]), "+f"(d[19]), "+f"(d[20]), "+f"(d[21]), "+f"(d[22]), "+f"(d[23]),
          "+f"(d[24]), "+f"(d[25]), "+f"(d[26]), "+f"(d[27]), "+f"(d[28]), "+f"(d[29]), "+f"(d[30]), "+f"(d[31]),
          "+f"(d[32]), "+f"(d[33]), "+f"(d[34]), "+f"(d[35]), "+f"(d[36]), "+f"(d[37]), "+f"(d[38]), "+f"(d[39]),
          "+f"(d[40]), "+f"(d[41]), "+f"(d[42]), "+f"(d[43]), "+f"(d[44]), "+f"(d[45]), "+f"(d[46]), "+f"(d[47]),
          "+f"(d[48]), "+f"(d[49]), "+f"(d[50]), "+f"(d[51]), "+f"(d[52]), "+f"(d[53]), "+f"(d[54]), "+f"(d[55]),
          "+f"(d[56]), "+f"(d[57]), "+f"(d[58]), "+f"(d[59]), "+f"(d[60]), "+f"(d[61]), "+f"(d[62]), "+f"(d[63])
        : "r"(a0), "r"(a1), "r"(a2), "r"(a3), "r"(db), "r"(scale_d));
}
__device__ __forceinline__ void wgmma_rs_n128_tb(float (&d)[64], uint32_t a0, uint32_t a1, uint32_t a2, uint32_t a3, uint32_t db, int scale_d) {
    asm volatile("{\n.reg .pred p;\n.reg .b64 da, db;\nsetp.ne.b32 p, %69, 0;\n"
        "mov.b64 db, {%68, 0x40000040};\n"
        "wgmma.mma_async.sync.aligned.m64n128k16.f32.bf16.bf16 "
        "{%0, %1, %2, %3, %4, %5, %6, %7, %8, %9, %10, %11, %12, %13, %14, %15, "
        "%16, %17, %18, %19, %20, %21, %22, %23, %24, %25, %26, %27, %28, %29, %30, %31, "
        "%32, %33, %34, %35, %36, %37, %38, %39, %40, %41, %42, %43, %44, %45, %46, %47, "
        "%48, %49, %50, %51, %52, %53, %54, %55, %56, %57, %58, %59, %60, %61, %62, %63}, "
        "{%64, %65, %66, %67}, db, p, 1, 1, 1;\n}"
        : "+f"(d[0]), "+f"(d[1]), "+f"(d[2]), "+f"(d[3]), "+f"(d[4]), "+f"(d[5]), "+f"(d[6]), "+f"(d[7]),
          "+f"(d[8]), "+f"(d[9]), "+f"(d[10]), "+f"(d[11]), "+f"(d[12]), "+f"(d[13]), "+f"(d[14]), "+f"(d[15]),
          "+f"(d[16]), "+f"(d[17]), "+f"(d[18]), "+f"(d[19]), "+f"(d[20]), "+f"(d[21]), "+f"(d[22]), "+f"(d[23]),
          "+f"(d[24]), "+f"(d[25]), "+f"(d[26]), "+f"(d[27]), "+f"(d[28]), "+f"(d[29]), "+f"(d[30]), "+f"(d[31]),
          "+f"(d[32]), "+f"(d[33]), "+f"(d[34]), "+f"(d[35]), "+f"(d[36]), "+f"(d[37]), "+f"(d[38]), "+f"(d[39]),
          "+f"(d[40]), "+f"(d[41]), "+f"(d[42]), "+f"(d[43]), "+f"(d[44]), "+f"(d[45]), "+f"(d[46]), "+f"(d[47]),
          "+f"(d[48]), "+f"(d[49]), "+f"(d[50]), "+f"(d[51]), "+f"(d[52]), "+f"(d[53]), "+f"(d[54]), "+f"(d[55]),
          "+f"(d[56]), "+f"(d[57]), "+f"(d[58]), "+f"(d[59]), "+f"(d[60]), "+f"(d[61]), "+f"(d[62]), "+f"(d[63])
        : "r"(a0), "r"(a1), "r"(a2), "r"(a3), "r"(db), "r"(scale_d));
}
__device__ __forceinline__ void wgmma_ss_n192_tb(float (&d)[96], uint32_t da, uint32_t db, int scale_d) {
    asm volatile("{\n.reg .pred p;\n.reg .b64 da, db;\nsetp.ne.b32 p, %98, 0;\n"
        "mov.b64 da, {%96, 0x40000040};\nmov.b64 db, {%97, 0x40000040};\n"
        "wgmma.mma_async.sync.aligned.m64n192k16.f32.bf16.bf16 "
        "{%0, %1, %2, %3, %4, %5, %6, %7, %8, %9, %10, %11, %12, %13, %14, %15, "
        "%16, %17, %18, %19, %20, %21, %22, %23, %24, %25, %26, %27, %28, %29, %30, %31, "
        "%32, %33, %34, %35, %36, %37, %38, %39, %40, %41, %42, %43, %44, %45, %46, %47, "
        "%48, %49, %50, %51, %52, %53, %54, %55, %56, %57, %58, %59, %60, %61, %62, %63, "
        "%64, %65, %66, %67, %68, %69, %70, %71, %72, %73, %74, %75, %76, %77, %78, %79, "
        "%80, %81, %82, %83, %84, %85, %86, %87, %88, %89, %90, %91, %92, %93, %94, %95}, "
        "da, db, p, 1, 1, 0, 1;\n}"
        : "+f"(d[0]), "+f"(d[1]), "+f"(d[2]), "+f"(d[3]), "+f"(d[4]), "+f"(d[5]), "+f"(d[6]), "+f"(d[7]),
          "+f"(d[8]), "+f"(d[9]), "+f"(d[10]), "+f"(d[11]), "+f"(d[12]), "+f"(d[13]), "+f"(d[14]), "+f"(d[15]),
          "+f"(d[16]), "+f"(d[17]), "+f"(d[18]), "+f"(d[19]), "+f"(d[20]), "+f"(d[21]), "+f"(d[22]), "+f"(d[23]),
          "+f"(d[24]), "+f"(d[25]), "+f"(d[26]), "+f"(d[27]), "+f"(d[28]), "+f"(d[29]), "+f"(d[30]), "+f"(d[31]),
          "+f"(d[32]), "+f"(d[33]), "+f"(d[34]), "+f"(d[35]), "+f"(d[36]), "+f"(d[37]), "+f"(d[38]), "+f"(d[39]),
          "+f"(d[40]), "+f"(d[41]), "+f"(d[42]), "+f"(d[43]), "+f"(d[44]), "+f"(d[45]), "+f"(d[46]), "+f"(d[47]),
          "+f"(d[48]), "+f"(d[49]), "+f"(d[50]), "+f"(d[51]), "+f"(d[52]), "+f"(d[53]), "+f"(d[54]), "+f"(d[55]),
          "+f"(d[56]), "+f"(d[57]), "+f"(d[58]), "+f"(d[59]), "+f"(d[60]), "+f"(d[61]), "+f"(d[62]), "+f"(d[63]),
          "+f"(d[64]), "+f"(d[65]), "+f"(d[66]), "+f"(d[67]), "+f"(d[68]), "+f"(d[69]), "+f"(d[70]), "+f"(d[71]),
          "+f"(d[72]), "+f"(d[73]), "+f"(d[74]), "+f"(d[75]), "+f"(d[76]), "+f"(d[77]), "+f"(d[78]), "+f"(d[79]),
          "+f"(d[80]), "+f"(d[81]), "+f"(d[82]), "+f"(d[83]), "+f"(d[84]), "+f"(d[85]), "+f"(d[86]), "+f"(d[87]),
          "+f"(d[88]), "+f"(d[89]), "+f"(d[90]), "+f"(d[91]), "+f"(d[92]), "+f"(d[93]), "+f"(d[94]), "+f"(d[95])
        : "r"(da), "r"(db), "r"(scale_d));
}

#define TSTAMP(i)
#define TSTAMP1(i)
#define TSTAMP_T(i, T)
#define CSTAMP(i)
#define ISTAMP(i)
#define FWRAP(k, stmt) do { stmt; } while (0)

template <int V> struct IC { static constexpr int value = V; };
template <int B, int E, class F> __device__ __forceinline__ void static_for(F&& f) {
    if constexpr (B < E) { f(IC<B>{}); static_for<B + 1, E>(f); }
}

#define PUBLISH(p) asm volatile("red.relaxed.gpu.global.add.u32 [%0], %1;" :: "l"(p), "r"(1u) : "memory")

constexpr float QSCALE = 0.08838834764831845f * 1.4426950408889634f;
#define G_PBASE0 1
#define G_PSTEP 4
constexpr int PSLAB = 5 * 256 * 16;
constexpr int XS_OFF = 7 * PSLAB;

struct Params {
    const __nv_bfloat16* x;
    __nv_bfloat16* out;
};

__device__ __forceinline__ void store_tile128(__nv_bfloat16* rowp  , size_t row8_stride,
                                              const float (&a)[64], float s0, float s1) {
#pragma unroll
    for (int m = 0; m < 4; m++) {
        uint4 v0, v1;
        v0.x = pack_bf16(a[16 * m + 0] * s0, a[16 * m + 1] * s0);
        v0.y = pack_bf16(a[16 * m + 4] * s0, a[16 * m + 5] * s0);
        v0.z = pack_bf16(a[16 * m + 8] * s0, a[16 * m + 9] * s0);
        v0.w = pack_bf16(a[16 * m + 12] * s0, a[16 * m + 13] * s0);
        v1.x = pack_bf16(a[16 * m + 2] * s1, a[16 * m + 3] * s1);
        v1.y = pack_bf16(a[16 * m + 6] * s1, a[16 * m + 7] * s1);
        v1.z = pack_bf16(a[16 * m + 10] * s1, a[16 * m + 11] * s1);
        v1.w = pack_bf16(a[16 * m + 14] * s1, a[16 * m + 15] * s1);
        *reinterpret_cast<uint4*>(rowp + 32 * m) = v0;
        *reinterpret_cast<uint4*>(rowp + row8_stride + 32 * m) = v1;
    }
}

template <int PIECE>
__device__ __forceinline__ void g_epi_piece(const float (&a)[64], int type, __nv_bfloat16* dst, int row8_stride, float rs0, float rs1) {
    asm volatile("" : "+f"(rs0), "+f"(rs1));
    if (type == 1) {
        constexpr int m = PIECE >> 1, rh = PIECE & 1;
        const float cexp = (rh ? rs1 : rs0) * -1.4426950408889634f;
        uint32_t o[4];
#pragma unroll
        for (int jj = 0; jj < 4; jj++) {
            const int gi = 16 * m + 4 * jj + 2 * rh;
            const uint32_t sg = pack_bf16(rcp(1.0f + ex2(a[gi] * cexp)), rcp(1.0f + ex2(a[gi + 1] * cexp)));
            o[jj] = hmul2_bf16(hmul2_bf16(pack_bf16(a[gi], a[gi + 1]), sg), pack_bf16(a[32 + gi], a[32 + gi + 1]));
        }
        *reinterpret_cast<uint4*>(dst + rh * row8_stride + 32 * m) = make_uint4(o[0], o[1], o[2], o[3]);
    } else if (type == 2) {
        constexpr int m = PIECE;
        uint4 v0, v1;
        rs0 *= QSCALE; rs1 *= QSCALE;
        v0.x = pack_bf16(a[16 * m + 0] * rs0, a[16 * m + 1] * rs0);
        v0.y = pack_bf16(a[16 * m + 2] * rs1, a[16 * m + 3] * rs1);
        v0.z = pack_bf16(a[16 * m + 4] * rs0, a[16 * m + 5] * rs0);
        v0.w = pack_bf16(a[16 * m + 6] * rs1, a[16 * m + 7] * rs1);
        v1.x = pack_bf16(a[16 * m + 8] * rs0, a[16 * m + 9] * rs0);
        v1.y = pack_bf16(a[16 * m + 10] * rs1, a[16 * m + 11] * rs1);
        v1.z = pack_bf16(a[16 * m + 12] * rs0, a[16 * m + 13] * rs0);
        v1.w = pack_bf16(a[16 * m + 14] * rs1, a[16 * m + 15] * rs1);
        *reinterpret_cast<uint4*>(dst + 32 * m) = v0;
        *reinterpret_cast<uint4*>(dst + row8_stride + 32 * m) = v1;
    }
}

struct GCtx {
    uint32_t a_lo, b_lo;
    uint32_t bars;
    int sg;
    float rs0, rs1;
    uint32_t lane0, ready;
    int pbase;
    uint32_t rbars, el;
};

__device__ __forceinline__ void g_stage(float (&acc)[64], GCtx& c, int kb, int accumulate) {
    const int s = c.sg & 3;
    if (!__all_sync(0xffffffffu, c.ready)) {
        mbar_wait_u(c.bars + (B_FULLG + s) * 8, (c.sg >> 2) & 1);
    }
    const uint32_t da = c.a_lo + kb * (SLOT >> 4);
    const uint32_t db = c.b_lo + s * (SLOT >> 4);
    wgmma_fence();
#pragma unroll
    for (int kk = 0; kk < 4; kk++)
        wgmma_ss_n128_tb(acc, da + kk * 2, db + kk * 128, kk != 0 ? 1 : accumulate);
    wgmma_commit();
    c.sg++;
    c.ready = mbar_probe(c.bars + (B_FULLG + (c.sg & 3)) * 8, (c.sg >> 2) & 1);
    wgmma_wait<1>();
    mbar_arrive_remote_if(c.rbars + (B_EMPTYG + ((c.sg - 2) & 3)) * 8, c.sg > 1 ? c.el : 0u);
}
__device__ __forceinline__ void g_tile(float (&acc)[64], float (&prev)[64], int ptype, __nv_bfloat16* pdst, int pstride,
                                       GCtx& c, uint32_t pub_bar) {
    g_stage(acc, c, 0, 0);
    fence_regs(prev);
#pragma unroll 1
    for (int kb = 1; kb < 10; kb++) {
        g_stage(acc, c, kb, 1);
        const int pc = kb - c.pbase;
        if (pc == 0) g_epi_piece<0>(prev, ptype, pdst, pstride, c.rs0, c.rs1);
        else if (pc == 1) g_epi_piece<1>(prev, ptype, pdst, pstride, c.rs0, c.rs1);
        else if (pc == 2) g_epi_piece<2>(prev, ptype, pdst, pstride, c.rs0, c.rs1);
        else if (pc == 3) {
            g_epi_piece<3>(prev, ptype, pdst, pstride, c.rs0, c.rs1);
            mbar_arrive_warp(pub_bar, pub_bar && c.lane0);
        }
    }
}

__global__ void __launch_bounds__(384, 1)
fused_kernel(const __grid_constant__ CUtensorMap tm_w1, const __grid_constant__ CUtensorMap tm_w3,
             const __grid_constant__ CUtensorMap tm_wq, const __grid_constant__ CUtensorMap tm_k,
             const __grid_constant__ CUtensorMap tm_v, const __grid_constant__ CUtensorMap tm_wo,
             const __grid_constant__ CUtensorMap tm_w2, const __grid_constant__ CUtensorMap tm_o,
             const __grid_constant__ CUtensorMap tm_h, const __grid_constant__ CUtensorMap tm_x,
             const __grid_constant__ CUtensorMap tm_out, const __grid_constant__ CUtensorMap tm_xs, const Params prm) {
    extern __shared__ __align__(1024) uint8_t smem_raw[];
    const uint32_t sbase = (smem_u32(smem_raw) + 1023) & ~1023u;
    const uint32_t bars = sbase + OFF_BAR;
    const int tid = threadIdx.x;
    const int warp = __shfl_sync(0xffffffffu, tid >> 5, 0);
    const int wg = warp >> 2;
    const int lane = tid & 31;
    const uint32_t rank = cluster_ctarank();
    const int cl = blockIdx.x >> 1;
    const int g = cl & 7;
    const int t = (cl >> 3) * 2 + (int)rank;
    const int nunits = (0x22344444u >> (4 * g)) & 15;
    const int ntiles = nunits + 4;
    const int ustart = g < 6 ? 4 * g : 23 + 2 * (g - 6) + (g == 6 ? 0 : 0);
    const int nblk = (int)((0x1b1b181614151415ull >> (8 * g)) & 255);
    unsigned* cnt = g_cnt + t * 128;

    TSTAMP(0);
    if (tid == 0) {
        for (int i = 0; i < 10; i++) mbar_init(bars + (B_X + i) * 8, 1);
        asm volatile("fence.mbarrier_init.release.cluster;" ::: "memory");
        for (int i = 0; i < 10; i++) {
            mbar_expect_tx(bars + (B_X + i) * 8, SLOT);
            tma_2d(sbase + i * SLOT, &tm_x, i * 64, t * 128, bars + (B_X + i) * 8);
        }
    } else if (tid == 64) {
        for (int i = 0; i < 4; i++) { mbar_init(bars + (B_FULLG + i) * 8, 1); mbar_init(bars + (B_EMPTYG + i) * 8, 4); }
        for (int i = 0; i < NP + 2; i++) { mbar_init(bars + (B_FULLA + i) * 8, 1); mbar_init(bars + (B_EMPTYA + i) * 8, 4); }
        for (int i = 0; i < 4; i++) { mbar_init(bars + (B_FULL3 + i) * 8, 1); mbar_init(bars + (B_EMPTY3 + i) * 8, 4); }
        mbar_init(bars + B_XNFREE * 8, 4);
        for (int i = 0; i < 8; i++) mbar_init(bars + (B_PUB + i) * 8, 8);
        for (int i = 0; i < 3; i++) mbar_init(bars + (B_IN + i) * 8, 1);
        mbar_init(bars + B_XS * 8, 1);
        asm volatile("fence.mbarrier_init.release.cluster;" ::: "memory");
    } else if (tid == 32) {
        prefetch_tmap(&tm_w1); prefetch_tmap(&tm_w3); prefetch_tmap(&tm_wq); prefetch_tmap(&tm_k); prefetch_tmap(&tm_v);
        prefetch_tmap(&tm_wo); prefetch_tmap(&tm_w2); prefetch_tmap(&tm_o); prefetch_tmap(&tm_h);
    }
    __syncthreads();
    cluster_arrive_relaxed();

    if (wg == 2) {
        asm volatile("setmaxnreg.dec.sync.aligned.u32 40;");
        cluster_wait();
        const unsigned epoch = (*(volatile unsigned*)cnt) >> 3;
        if (warp == 8 && lane == 0) {
            const int nG = 10 * ntiles;
            auto coords = [&](int s, const CUtensorMap*& m, int& c0, int& c1) {
                if (s < nG) {
                    const int tile = s / 10, kb = s - tile * 10;
                    if (tile < nunits) { m = rank ? &tm_w3 : &tm_w1; c0 = (ustart + tile) * 64; }
                    else { m = &tm_wq; c0 = (4 * g + ((tile - nunits + 1) & 3)) * 128 + rank * 64; }
                    c1 = kb * 64;
                } else {
                    const int n = s - nG;
                    int isv, it, half;
                    if (n < 2) { isv = 0; it = 0; half = n; }
                    else if (n >= 62) { isv = 1; it = 15; half = n - 62; }
                    else { const int q = (n - 2) >> 2, r = (n - 2) & 3; isv = r >> 1; it = q + 1 - isv; half = r & 1; }
                    const int kv0 = (4 * g + (it >> 2)) * SKV + KOFF + (it & 3) * 128;
                    if (isv) { m = &tm_v; c0 = rank * 64; c1 = kv0 + half * 64; }
                    else { m = &tm_k; c0 = half * 64; c1 = kv0 + rank * 64; }
                }
            };
            const int nh = g & 1, kq = g >> 1;
            const CUtensorMap* mb = (kq == 3) ? &tm_w2 : &tm_wo;
            const int pidx = cl >> 3;
            auto prefetch = [&](int s) {
            };
#define PF_DIST 16
            for (int s = 4; s < PF_DIST; s++) prefetch(s);
            int sg = 0;
            for (; sg < nG; sg++) {
                const CUtensorMap* m; int c0, c1;
                coords(sg, m, c0, c1);
                const int s = sg & 3;
                mbar_wait(bars + (B_EMPTYG + s) * 8, ((sg >> 2) & 1) ^ 1, 10);
                mbar_expect_tx(bars + (B_FULLG + s) * 8, SLOT);
                tma_2d_mc(sbase + OFF_RINGG + s * SLOT + rank * 8192, m, c0, c1, bars + (B_FULLG + s) * 8);
                prefetch(sg + PF_DIST);
            }
            int sa = 0, pa = 0;
            for (int T = 0; T < 32; T++) {
                uint32_t dst, fb;
                if (T < 2) {
                    for (int v = 0; v < 2; v++) mbar_wait(bars + (B_EMPTYG + ((sg + v) & 3)) * 8, (((sg + v) >> 2) & 1) ^ 1, 11);
                    dst = sbase + OFF_RINGG + (sg & 3) * SLOT; fb = bars + (B_FULLA + NP + T) * 8;
                    sg += 2;
                } else {
                    if (T == 2) mbar_wait(bars + B_XNFREE * 8, 0, 12);
                    if (T >= 2 + NP) mbar_wait(bars + (B_EMPTYA + sa) * 8, pa ^ 1, 13);
                    dst = sbase + sa * 2 * SLOT; fb = bars + (B_FULLA + sa) * 8;
                    if (++sa == NP) { sa = 0; pa ^= 1; }
                }
                mbar_expect_tx(fb, 2 * SLOT);
                for (int v = 0; v < 2; v++) {
                    const CUtensorMap* m; int c0, c1;
                    coords(nG + 2 * T + v, m, c0, c1);
                    tma_2d_mc(dst + v * SLOT + rank * 8192, m, c0, c1, fb);
                    prefetch(nG + 2 * T + v + PF_DIST);
                }
            }
            const CUtensorMap* ma = (kq == 3) ? &tm_h : &tm_o;
            int round_ok = -1;
            for (int i = 0; i < nblk; i++) {
                const int st = i & 3;
                if (i == 0) { mbar_wait(bars + (B_EMPTYA + NP) * 8, 0, 14); mbar_wait(bars + (B_EMPTYA + NP + 1) * 8, 0, 14); }
                else if (i == 1) { mbar_wait(bars + (B_EMPTYA + 0) * 8, pa ^ 1, 15); mbar_wait(bars + (B_EMPTYA + 1) * 8, pa ^ 1, 15); }
                else if (i == 2) { mbar_wait(bars + (B_EMPTYA + 2) * 8, pa ^ 1, 15); mbar_wait(bars + (B_EMPTYA + 3) * 8, pa ^ 1, 15); }
                else if (i == 3) mbar_wait(bars + (B_EMPTYA + 4) * 8, pa ^ 1, 15);
                else mbar_wait(bars + (B_EMPTY3 + st) * 8, ((i >> 2) & 1) ^ 1, 18);
                const int b = c_blk[g][i];
                const int round = (kq == 3) ? 0 : ((b >> 1) & 3);
                if (round != round_ok) {
                    if (kq == 3) wait_flag(cnt, (epoch + 1) * 8, 19);
                    else wait_flag(cnt + 8 + round * 8, (epoch + 1) * 8, 20);
                    asm volatile("fence.proxy.async;" ::: "memory");
                    round_ok = round;
                }
                const uint32_t base = sbase + ((st + 3) & 3) * ST3;
                const uint32_t fb = bars + (B_FULL3 + st) * 8;
                mbar_expect_tx(fb, ST3);
                tma_5d_mc(base + SLOT + rank * 20480, mb, b * 8 + rank * 4, nh * 5, fb);
                tma_2d(base, ma, b * 64, t * 128, fb);
                prefetch(nG + 64 + i + PF_DIST);
            }
            for (int i = nblk; i < nblk + 4; i++)
                mbar_wait(bars + (B_EMPTY3 + (i & 3)) * 8, ((i >> 2) & 1) ^ 1, 21);
            mbar_expect_tx(bars + B_XS * 8, PSLAB);
            tma_2d(sbase + XS_OFF, &tm_xs, nh * 320 + kq * 80, t * 128, bars + B_XS * 8);
            for (int e = 0; e < 4; e++) {
                const int src = (e + 3) & 3;
                if (src == kq) continue;
                const int d = src < kq ? src : src - 1;
                wait_flag(cnt + 64 + nh * 16 + kq * 4 + src, epoch + 1, 22);
                TSTAMP1(22 + d);
                asm volatile("fence.proxy.async;" ::: "memory");
                mbar_expect_tx(bars + (B_IN + d) * 8, PSLAB);
                bulk_load(sbase + (4 + d) * PSLAB, g_part + (size_t)(((t * 2 + nh) * 4 + src) * 4 + kq) * (PSLAB / 16), PSLAB, bars + (B_IN + d) * 8);
            }
        } else if (warp == 9 && lane == 0) {
            for (int ev = 0; ev < 5; ev++) {
                mbar_wait(bars + (B_PUB + ev) * 8, 0, 30);
                asm volatile("fence.proxy.async;" ::: "memory");
                __threadfence();
                red_release(ev == 0 ? cnt : cnt + 8 * ev, 1);
            }
            {
                const int nh = g & 1, kq = g >> 1;
                uint4* part = g_part + (size_t)((t * 2 + nh) * 4 + kq) * 4 * (PSLAB / 16);
                mbar_wait(bars + (B_PUB + 5) * 8, 0, 31);
                for (int d = 1; d < 4; d++)
                    bulk_store(part + ((kq + d) & 3) * (PSLAB / 16), sbase + ((kq + d) & 3) * PSLAB, PSLAB);
                unsigned* fl = cnt + 64 + nh * 16 + kq;
                TSTAMP1(16);
                bulk_wait<2>();
                TSTAMP1(17);
                PUBLISH(fl + ((kq + 1) & 3) * 4);
                TSTAMP1(18);
                bulk_wait<1>();
                TSTAMP1(19);
                PUBLISH(fl + ((kq + 2) & 3) * 4);
                bulk_wait<0>();
                TSTAMP1(20);
                PUBLISH(fl + ((kq + 3) & 3) * 4);
                TSTAMP1(21);
            }
        }
    } else {
        asm volatile("setmaxnreg.inc.sync.aligned.u32 232;");
        TSTAMP(7);
        const int wl = warp & 3;
        const int q4 = lane & 3;
        const uint32_t el = ((tid & 127) == 0 || (tid & 127) == 32) ? 1u : 0u;
        const uint32_t rbars = mapa_u32(bars, (tid & 127) == 32 ? 1u : 0u);
        const int row0 = t * 128 + wg * 64 + wl * 16 + (lane >> 2);

        float rs0, rs1;
        {
            const int g8 = lane >> 2;
            const int ra = wg * 64 + wl * 16 + g8;
            uint32_t xa[80], xb[80];
            float sm[2][4] = {{0.f, 0.f, 0.f, 0.f}, {0.f, 0.f, 0.f, 0.f}};
            float ga[2][4] = {{0.f, 0.f, 0.f, 0.f}, {0.f, 0.f, 0.f, 0.f}}, gb[2][4] = {{0.f, 0.f, 0.f, 0.f}, {0.f, 0.f, 0.f, 0.f}};
            uint32_t sha = 0, shb = 0;
#pragma unroll
            for (int m = 0; m < 10; m++) {
                mbar_wait_u(bars + (B_X + m) * 8, 0);
#pragma unroll
                for (int ii = 0; ii < 2; ii++) {
                    const int i = 2 * m + ii;
                    const int c = q4 + 4 * (i ^ (g8 & 1));
                    const uint32_t src = sbase + m * SLOT + ra * 128 + (((c & 7) ^ (ra & 7)) << 4);
                    asm volatile("ld.shared.v4.b32 {%0, %1, %2, %3}, [%4];" : "=r"(xa[4 * i]), "=r"(xa[4 * i + 1]), "=r"(xa[4 * i + 2]), "=r"(xa[4 * i + 3]) : "r"(src) : "memory");
                    asm volatile("ld.shared.v4.b32 {%0, %1, %2, %3}, [%4];" : "=r"(xb[4 * i]), "=r"(xb[4 * i + 1]), "=r"(xb[4 * i + 2]), "=r"(xb[4 * i + 3]) : "r"(src + 8 * 128) : "memory");
                }
                if (m == 0) {
                    const uint32_t ea = (g8 & 1) ? xa[4] : xa[0], eb = (g8 & 1) ? xb[4] : xb[0];
                    sha = __shfl_sync(0xffffffffu, ea, lane & ~3); shb = __shfl_sync(0xffffffffu, eb, lane & ~3);
                    sha = __byte_perm(sha, sha, 0x1010); shb = __byte_perm(shb, shb, 0x1010);
                }
#pragma unroll
                for (int u = 0; u < 4; u++) {
                    const int e = 8 * m + 2 * u;
                    const uint32_t a0 = hsub2_bf16(xa[e], sha), a2 = hsub2_bf16(xa[e + 1], sha);
                    const uint32_t a1 = hsub2_bf16(xb[e], shb), a3 = hsub2_bf16(xb[e + 1], shb);
                    mma_bf16(sm[u & 1], a0, a1, a2, a3, 0x3F803F80u, 0x3F803F80u);
                    mma_bf16(ga[u & 1], a0, a1, a2, a3, a0, a2);
                    mma_bf16(gb[u & 1], a0, a1, a2, a3, a1, a3);
                }
            }
            TSTAMP(9);
            const float ea1 = (sm[0][0] + sm[1][0]) * (1.0f / DM), eb1 = (sm[0][2] + sm[1][2]) * (1.0f / DM);
            const float mean_a = bf_lo(sha) + ea1, mean_b = bf_lo(shb) + eb1;
            const uint32_t mab = pack_bf16(mean_a, mean_b);
            const uint32_t ma2 = __byte_perm(mab, mab, 0x1010), mb2 = __byte_perm(mab, mab, 0x3232);
            const int dl = 4 * g8 + (g8 >> 1);
            const float sqa = __shfl_sync(0xffffffffu, (g8 & 1) ? ga[0][1] + ga[1][1] : ga[0][0] + ga[1][0], dl);
            const float sqb = __shfl_sync(0xffffffffu, (g8 & 1) ? gb[0][3] + gb[1][3] : gb[0][2] + gb[1][2], dl);
            TSTAMP(10);
            const float var_a = bf_round(fmaxf(sqa * (1.0f / DM) - ea1 * ea1, 0.f));
            const float var_b = bf_round(fmaxf(sqb * (1.0f / DM) - eb1 * eb1, 0.f));
            const float inv_a = 1.0f / bf_round(sqrtf(bf_round(var_a + 1e-5f)));
            const float inv_b = 1.0f / bf_round(sqrtf(bf_round(var_b + 1e-5f)));
            rs0 = inv_a; rs1 = inv_b;
#pragma unroll
            for (int i = 0; i < 20; i++) {
                uint32_t oa[4], ob[4];
#pragma unroll
                for (int e = 0; e < 4; e++) {
                    oa[e] = hsub2_bf16(xa[4 * i + e], ma2);
                    ob[e] = hsub2_bf16(xb[4 * i + e], mb2);
                }
                const int c = q4 + 4 * (i ^ (g8 & 1));
                const uint32_t dst = sbase + (c >> 3) * SLOT + ra * 128 + (((c & 7) ^ (ra & 7)) << 4);
                asm volatile("st.shared.v4.b32 [%0], {%1, %2, %3, %4};" :: "r"(dst), "r"(oa[0]), "r"(oa[1]), "r"(oa[2]), "r"(oa[3]) : "memory");
                asm volatile("st.shared.v4.b32 [%0], {%1, %2, %3, %4};" :: "r"(dst + 8 * 128), "r"(ob[0]), "r"(ob[1]), "r"(ob[2]), "r"(ob[3]) : "memory");
            }
            TSTAMP(11);
            asm volatile("fence.proxy.async.shared::cta;" ::: "memory");
            named_sync(3 + wg, 128);
            TSTAMP(12);
            cluster_wait();
        }
        TSTAMP(1);

        CSTAMP(14);
        GCtx c;
        c.a_lo = desc_lo(sbase + wg * 8192, 16); c.b_lo = desc_lo(sbase + OFF_RINGG, 8192); c.bars = bars; c.sg = 0; c.rbars = rbars; c.el = el; c.rs0 = rs0; c.rs1 = rs1; c.lane0 = lane == 0; c.ready = 0; c.pbase = G_PBASE0 + G_PSTEP * wg;
        uint32_t qf[32];
        {
            float accA[64], accB[64];
#pragma unroll
            for (int i = 0; i < 64; i++) { asm volatile("" : "=f"(accA[i])); asm volatile("" : "=f"(accB[i])); }
            __nv_bfloat16* const hrow = g_h + (size_t)row0 * FF + 8 * q4;
            __nv_bfloat16* const qrow = g_oq + (size_t)row0 * (NH * DH) + 8 * q4;
            auto epi_type = [&](int i) { return i < 0 ? 0 : (i < nunits ? 1 : 2); };
            auto epi_dst = [&](int i) {
                return i < nunits ? hrow + (ustart + i) * 64 : qrow + (4 * g + ((i - nunits + 1) & 3)) * 128;
            };
            auto epi_stride = [&](int i) { return i < nunits ? 8 * FF : 8 * NH * DH; };
            auto epi_pub = [&](int i) { return (i == nunits - 1) ? bars + B_PUB * 8 : 0u; };
#pragma unroll 1
            for (int i = (ntiles & 1) ? -1 : 0; i < ntiles; i += 2) {
                if (i >= 0) g_tile(accA, accB, epi_type(i - 1), epi_dst(i - 1), epi_stride(i - 1), c, epi_pub(i - 1));
                g_tile(accB, accA, epi_type(i), epi_dst(i), epi_stride(i), c, epi_pub(i));
            }
            wgmma_wait<0>();
            fence_regs(accB);
            mbar_arrive_remote_if(rbars + (B_EMPTYG + ((c.sg - 1) & 3)) * 8, el);
            mbar_arrive_remote_if(rbars + B_XNFREE * 8, el);
#pragma unroll
            for (int j = 0; j < 16; j++) {
                qf[2 * j] = pack_bf16(accB[4 * j] * (rs0 * QSCALE), accB[4 * j + 1] * (rs0 * QSCALE));
                qf[2 * j + 1] = pack_bf16(accB[4 * j + 2] * (rs1 * QSCALE), accB[4 * j + 3] * (rs1 * QSCALE));
            }
        }
        TSTAMP(2);
        CSTAMP(15);

        {
            float sacc[64], oacc[64];
            uint32_t pf[32];
            float m0 = 0.f, m1 = 0.f, l0 = 0.f, l1 = 0.f, sc0 = 1.f, sc1 = 1.f, pl0 = 0.f, pl1 = 0.f;
            bool gen = false;
            auto rel = [&](uint32_t idx) { mbar_arrive_remote_if(rbars + idx * 8, el); };
#define WAITA2(a, b, c, d) mbar_wait2(a, b, c, d)
            int sa = 0;
            uint32_t pa = 0;
            auto adv = [&]() { const bool w = sa == NP - 1; sa = w ? 0 : sa + 1; pa ^= w ? 1u : 0u; };

            auto issue_qk = [&](uint32_t a0, uint32_t a1) {
                wgmma_fence();
#pragma unroll
                for (int kk = 0; kk < 4; kk++)
                    wgmma_rs_n128_kb(sacc, qf[4 * kk], qf[4 * kk + 1], qf[4 * kk + 2], qf[4 * kk + 3], a0 + kk * 2, kk != 0);
#pragma unroll
                for (int kk = 4; kk < 8; kk++)
                    wgmma_rs_n128_kb(sacc, qf[4 * kk], qf[4 * kk + 1], qf[4 * kk + 2], qf[4 * kk + 3], a1 + (kk - 4) * 2, 1);
                wgmma_commit();
            };
            auto issue_pv = [&](uint32_t a0, uint32_t a1, int acc_flag) {
                a0 = desc_lo(a0, 8192); a1 = desc_lo(a1, 8192);
                wgmma_fence();
#pragma unroll
                for (int kk = 0; kk < 4; kk++)
                    wgmma_rs_n128_tb(oacc, pf[4 * kk], pf[4 * kk + 1], pf[4 * kk + 2], pf[4 * kk + 3], a0 + kk * 128, kk != 0 ? 1 : acc_flag);
#pragma unroll
                for (int kk = 4; kk < 8; kk++)
                    wgmma_rs_n128_tb(oacc, pf[4 * kk], pf[4 * kk + 1], pf[4 * kk + 2], pf[4 * kk + 3], a1 + (kk - 4) * 128, 1);
                wgmma_commit();
            };
            auto rowmax = [&](float& x0, float& x1) {
                float a[4], b[4];
#pragma unroll
                for (int u = 0; u < 4; u++) {
                    a[u] = fmaxf(sacc[4 * u], sacc[4 * u + 1]);
                    b[u] = fmaxf(sacc[4 * u + 2], sacc[4 * u + 3]);
                }
#pragma unroll
                for (int j = 4; j < 16; j++) {
                    a[j & 3] = fmaxf(a[j & 3], fmaxf(sacc[4 * j], sacc[4 * j + 1]));
                    b[j & 3] = fmaxf(b[j & 3], fmaxf(sacc[4 * j + 2], sacc[4 * j + 3]));
                }
                x0 = fmaxf(fmaxf(a[0], a[1]), fmaxf(a[2], a[3]));
                x1 = fmaxf(fmaxf(b[0], b[1]), fmaxf(b[2], b[3]));
                x0 = fmaxf(x0, __shfl_xor_sync(0xffffffffu, x0, 1));
                x1 = fmaxf(x1, __shfl_xor_sync(0xffffffffu, x1, 1));
                x0 = fmaxf(x0, __shfl_xor_sync(0xffffffffu, x0, 2));
                x1 = fmaxf(x1, __shfl_xor_sync(0xffffffffu, x1, 2));
            };
            auto out_of_range = [&](bool first) {
                int a = __vimax3_s32(__float_as_int(sacc[0]), __float_as_int(sacc[1]), __float_as_int(sacc[2]));
                int b = __vimax3_s32(__float_as_int(sacc[3]), __float_as_int(sacc[4]), __float_as_int(sacc[5]));
                int c2 = __vimax3_s32(__float_as_int(sacc[6]), __float_as_int(sacc[7]), __float_as_int(sacc[8]));
                int d2 = __vimax3_s32(__float_as_int(sacc[9]), __float_as_int(sacc[10]), __float_as_int(sacc[11]));
#pragma unroll
                for (int i = 12; i < 60; i += 8) {
                    a = __vimax3_s32(a, __float_as_int(sacc[i]), __float_as_int(sacc[i + 1]));
                    b = __vimax3_s32(b, __float_as_int(sacc[i + 2]), __float_as_int(sacc[i + 3]));
                    c2 = __vimax3_s32(c2, __float_as_int(sacc[i + 4]), __float_as_int(sacc[i + 5]));
                    d2 = __vimax3_s32(d2, __float_as_int(sacc[i + 6]), __float_as_int(sacc[i + 7]));
                }
                a = __vimax3_s32(a, __float_as_int(sacc[60]), __float_as_int(sacc[61]));
                b = __vimax3_s32(b, __float_as_int(sacc[62]), __float_as_int(sacc[63]));
                bool bad = __vimax3_s32(a, b, max(c2, d2)) > 0x42800000;
                if (first) {
                    unsigned u0 = min(__float_as_uint(sacc[0]), __float_as_uint(sacc[1]));
                    unsigned u1 = min(__float_as_uint(sacc[2]), __float_as_uint(sacc[3]));
#pragma unroll
                    for (int j = 1; j < 16; j++) {
                        u0 = __vimin3_u32(u0, __float_as_uint(sacc[4 * j]), __float_as_uint(sacc[4 * j + 1]));
                        u1 = __vimin3_u32(u1, __float_as_uint(sacc[4 * j + 2]), __float_as_uint(sacc[4 * j + 3]));
                    }
                    bad = bad || max(u0, u1) > 0xC2800000u;
                }
                return __any_sync(0xffffffffu, bad) != 0;
            };
            auto exp_part = [&](auto J0_, auto J1_, float& t0, float& t1, float& u0, float& u1) {
#pragma unroll
                for (int j = decltype(J0_)::value; j < decltype(J1_)::value; j++) {
                    sacc[4 * j] = ex2(sacc[4 * j]); sacc[4 * j + 1] = ex2(sacc[4 * j + 1]);
                    sacc[4 * j + 2] = ex2(sacc[4 * j + 2]); sacc[4 * j + 3] = ex2(sacc[4 * j + 3]);
                    t0 += sacc[4 * j]; u0 += sacc[4 * j + 1];
                    t1 += sacc[4 * j + 2]; u1 += sacc[4 * j + 3];
                }
            };
            auto o_epilogue = [&](int hi, float a, float b) {
                store_tile128(g_oq + (size_t)row0 * (NH * DH) + (4 * g + hi) * 128 + 8 * q4, (size_t)8 * NH * DH, oacc, a, b);
                mbar_arrive_warp(bars + (B_PUB + 1 + hi) * 8, lane == 0);
            };
            constexpr int SPLIT = 12;
            if (wg == 1) named_arrive(1, 256);
#define PP_SYNC() named_sync(1 + wg, 256)
#define PP_ARRIVE() named_arrive(2 - wg, 256)
            const int sg0 = 10 * ntiles;
            uint32_t ka = desc_lo(sbase + OFF_RINGG + (sg0 & 3) * SLOT, 16);
            uint32_t kr = B_EMPTYA + NP;
            FWRAP(8, mbar_wait_u(bars + (B_FULLA + NP) * 8, 0));
#pragma unroll
            for (int i = 0; i < 64; i++) { asm volatile("" : "=f"(oacc[i])); asm volatile("" : "=f"(sacc[i])); }
#pragma unroll
            for (int i = 0; i < 32; i++) asm volatile("" : "=r"(pf[i]));
#pragma unroll 1
            for (int it = 0; it < 16; it++) {
                const int j = it & 3;
                ISTAMP(it);
                FWRAP(0, PP_SYNC());
                FWRAP(7, issue_qk(ka, ka + (SLOT >> 4)));
                const uint32_t kc = kr;
                const int va = sa; const uint32_t vp = pa;
                if (it > 0) adv();
                uint32_t nf = B_FULLA + NP + 1, np = 0;
                if (it == 0) {
                    ka = desc_lo(sbase + OFF_RINGG + ((sg0 + 2) & 3) * SLOT, 16); kr = B_EMPTYA + NP + 1;
                } else if (it < 15) {
                    nf = B_FULLA + sa; np = pa;
                    ka = desc_lo(sbase + sa * 2 * SLOT, 16); kr = B_EMPTYA + sa;
                    adv();
                }
                if (j == 1 && it > 1) o_epilogue((it >> 2) - 1, pl0, pl1);
                FWRAP(1, mbar_wait2(bars + (it > 0 ? B_FULLA + va : nf) * 8, it > 0 ? vp : np,
                                    bars + (it < 15 ? nf : B_FULLA + va) * 8, it < 15 ? np : vp));
                const __nv_bfloat16* qsrc = g_oq + (size_t)row0 * (NH * DH) + (4 * g + (it >> 2) + 1) * 128 + 8 * q4;
                if (j == 2 && it < 14) {
                    asm volatile("prefetch.global.L1 [%0];" :: "l"(qsrc));
                    asm volatile("prefetch.global.L1 [%0];" :: "l"(qsrc + 64));
                    asm volatile("prefetch.global.L1 [%0];" :: "l"(qsrc + (size_t)8 * NH * DH));
                    asm volatile("prefetch.global.L1 [%0];" :: "l"(qsrc + (size_t)8 * NH * DH + 64));
                }
                if (it > 0) FWRAP(2, issue_pv(sbase + va * 2 * SLOT, sbase + (va * 2 + 1) * SLOT, j != 1));
                else wgmma_commit();
                PP_ARRIVE();
                FWRAP(3, wgmma_wait<1>());
                fence_regs(sacc);
                float t0 = 0.f, t1 = 0.f, u0 = 0.f, u1 = 0.f;
                {
                    rel(kc);
                    if (j == 3 && it < 15) {
#pragma unroll
                        for (int m = 0; m < 4; m++) {
                            uint4 u0 = *reinterpret_cast<const uint4*>(qsrc + 32 * m);
                            uint4 u1 = *reinterpret_cast<const uint4*>(qsrc + (size_t)8 * NH * DH + 32 * m);
                            qf[8 * m + 0] = u0.x; qf[8 * m + 1] = u0.y; qf[8 * m + 2] = u0.z; qf[8 * m + 3] = u0.w;
                            qf[8 * m + 4] = u1.x; qf[8 * m + 5] = u1.y; qf[8 * m + 6] = u1.z; qf[8 * m + 7] = u1.w;
                        }
                    }
                    if (j == 0) { l0 = 0.f; l1 = 0.f; m0 = 0.f; m1 = 0.f; gen = false; }
                    if (!gen) gen = out_of_range(j == 0);
                    if (gen) {
                        float x0, x1;
                        rowmax(x0, x1);
                        if (j != 0) {
                            x0 = fmaxf(x0, m0); x1 = fmaxf(x1, m1);
                            sc0 = ex2(m0 - x0); sc1 = ex2(m1 - x1);
                            l0 *= sc0; l1 *= sc1;
                        }
                        m0 = x0; m1 = x1;
#pragma unroll
                        for (int jj = 0; jj < 16; jj++) {
                            sacc[4 * jj] -= m0; sacc[4 * jj + 1] -= m0;
                            sacc[4 * jj + 2] -= m1; sacc[4 * jj + 3] -= m1;
                        }
                    }
                    exp_part(IC<0>{}, IC<SPLIT>{}, t0, t1, u0, u1);
                }
                asm volatile("st.shared.f32 [%0], %1;" :: "r"(bars + 512), "f"((t0 + u0) + (t1 + u1)) : "memory");
                FWRAP(5, wgmma_wait<0>());
                fence_regs(oacc);
                fence_regs(pf);
                if (it > 0) rel(B_EMPTYA + va);
                {
                    exp_part(IC<SPLIT>{}, IC<16>{}, t0, t1, u0, u1);
                    l0 += t0 + u0; l1 += t1 + u1;
#pragma unroll
                    for (int jj = 0; jj < 16; jj++) {
                        pf[2 * jj] = pack_bf16(sacc[4 * jj], sacc[4 * jj + 1]);
                        pf[2 * jj + 1] = pack_bf16(sacc[4 * jj + 2], sacc[4 * jj + 3]);
                    }
                    if (j != 0 && gen) {
#pragma unroll
                        for (int jj = 0; jj < 16; jj++) {
                            oacc[4 * jj] *= sc0; oacc[4 * jj + 1] *= sc0;
                            oacc[4 * jj + 2] *= sc1; oacc[4 * jj + 3] *= sc1;
                        }
                    }
                    if (j == 3) {
                        float a = l0, b = l1;
                        a += __shfl_xor_sync(0xffffffffu, a, 1); b += __shfl_xor_sync(0xffffffffu, b, 1);
                        a += __shfl_xor_sync(0xffffffffu, a, 2); b += __shfl_xor_sync(0xffffffffu, b, 2);
                        pl0 = rcp(a); pl1 = rcp(b);
                    }
                }
            }
            {
                ISTAMP(16);
                mbar_wait_u(bars + (B_FULLA + NP - 1) * 8, 1);
                PP_SYNC();
                issue_pv(sbase + (NP - 1) * 2 * SLOT, sbase + ((NP - 1) * 2 + 1) * SLOT, 1);
                if (wg == 0) named_arrive(2, 256);
                wgmma_wait<0>();
                fence_regs(oacc);
                rel(B_EMPTYA + NP - 1);
            }
            ISTAMP(17);
            o_epilogue(3, pl0, pl1);
            ISTAMP(18);
            CSTAMP(13);
        }
        TSTAMP(3);

        {
            float a192[96], a128[64];
#pragma unroll 1
            for (int i = 0; i < nblk; i++) {
                const int st = i & 3;
                mbar_wait_u(bars + (B_FULL3 + st) * 8, (i >> 2) & 1);
                const uint32_t base = sbase + ((st + 3) & 3) * ST3;
                const uint32_t da = desc_lo(base + wg * 8192, 16);
                const uint32_t db = desc_lo(base + SLOT, 4096);
                wgmma_fence();
#pragma unroll
                for (int kk = 0; kk < 4; kk++) {
                    const uint32_t bb = db + (kk >> 1) * (20480 >> 4) + (kk & 1) * (2048 >> 4);
                    wgmma_ss_n192_tb(a192, da + kk * 2, bb, (i | kk) != 0);
                    wgmma_ss_n128_tb(a128, da + kk * 2, bb + ((3 * 4096) >> 4), (i | kk) != 0);
                }
                wgmma_commit();
                if (i > 0) {
                    wgmma_wait<1>();
                    mbar_arrive_remote_if(rbars + (B_EMPTY3 + ((i - 1) & 3)) * 8, el);
                }
            }
            wgmma_wait<0>();
            fence_regs(a192);
            fence_regs(a128);
            mbar_arrive_remote_if(rbars + (B_EMPTY3 + ((nblk - 1) & 3)) * 8, el);
            TSTAMP(4);
            CSTAMP(0);
            TSTAMP_T(30, 128);

            const int kq = g >> 1;
            named_sync(5, 256);
            CSTAMP(1);
            static_for<0, 20>([&](auto I_) {
                constexpr int i = decltype(I_)::value;
                uint32_t w[4];
                static_for<0, 2>([&](auto H_) {
                    constexpr int jn = 2 * i + decltype(H_)::value;
                    if constexpr (jn < 24) {
                        w[2 * decltype(H_)::value] = pack_bf16(a192[4 * jn], a192[4 * jn + 1]);
                        w[2 * decltype(H_)::value + 1] = pack_bf16(a192[4 * jn + 2], a192[4 * jn + 3]);
                    } else {
                        w[2 * decltype(H_)::value] = pack_bf16(a128[4 * (jn - 24)], a128[4 * (jn - 24) + 1]);
                        w[2 * decltype(H_)::value + 1] = pack_bf16(a128[4 * (jn - 24) + 2], a128[4 * (jn - 24) + 3]);
                    }
                });
                asm volatile("st.shared.v4.b32 [%0], {%1, %2, %3, %4};"
                             :: "r"(sbase + (i * 256 + tid) * 16), "r"(w[0]), "r"(w[1]), "r"(w[2]), "r"(w[3]) : "memory");
            });
            CSTAMP(2);
            asm volatile("fence.proxy.async.shared::cta;" ::: "memory");
            CSTAMP(3);
            mbar_arrive_warp(bars + (B_PUB + 5) * 8, lane == 0);
            CSTAMP(4);
            TSTAMP(5);
            auto src_addr = [&](int src) { return sbase + (src == kq ? kq : 4 + (src < kq ? src : src - 1)) * PSLAB + tid * 16; };
            auto src_bar = [&](int src) { return bars + (B_IN + (src < kq ? src : src - 1)) * 8; };
            if (kq != 3) mbar_wait_u(src_bar(3), 0);
            TSTAMP(25);
            CSTAMP(5);
            {
                const uint32_t ga = src_addr(3);
#pragma unroll 1
                for (int i = 0; i < 5; i++) {
                    uint32_t w[4];
                    asm volatile("ld.shared.v4.b32 {%0, %1, %2, %3}, [%4];" : "=r"(w[0]), "=r"(w[1]), "=r"(w[2]), "=r"(w[3]) : "r"(ga + i * 4096) : "memory");
#pragma unroll
                    for (int e = 0; e < 4; e++) {
                        const float r2 = (e & 1) ? rs1 * rs1 : rs0 * rs0;
                        const uint32_t gb = pack_bf16(bf_lo(w[e]) * r2, bf_hi(w[e]) * r2);
                        w[e] = pack_bf16(silu_f(bf_lo(gb)), silu_f(bf_hi(gb)));
                    }
                    asm volatile("st.shared.v4.b32 [%0], {%1, %2, %3, %4};" :: "r"(ga + i * 4096), "r"(w[0]), "r"(w[1]), "r"(w[2]), "r"(w[3]) : "memory");
                }
            }
            mbar_wait_u(bars + B_XS * 8, 0);
#pragma unroll 1
            for (int v = 0; v < 3; v++) if (v != kq) mbar_wait_u(src_bar(v), 0);
            TSTAMP(27);
            CSTAMP(6); CSTAMP(7);
            {
                const uint32_t s0a = src_addr(0), s1a = src_addr(1), s2a = src_addr(2), ga = src_addr(3);
                const uint32_t xs = sbase + XS_OFF + (wg * 64 + wl * 16 + (lane >> 2)) * 160 + q4 * 4;
#pragma unroll 1
                for (int i = 0; i < 5; i++) {
                    uint32_t p0[4], p1[4], p2[4], a[4], x[4];
                    asm volatile("ld.shared.v4.b32 {%0, %1, %2, %3}, [%4];" : "=r"(p0[0]), "=r"(p0[1]), "=r"(p0[2]), "=r"(p0[3]) : "r"(s0a + i * 4096) : "memory");
                    asm volatile("ld.shared.v4.b32 {%0, %1, %2, %3}, [%4];" : "=r"(p1[0]), "=r"(p1[1]), "=r"(p1[2]), "=r"(p1[3]) : "r"(s1a + i * 4096) : "memory");
                    asm volatile("ld.shared.v4.b32 {%0, %1, %2, %3}, [%4];" : "=r"(p2[0]), "=r"(p2[1]), "=r"(p2[2]), "=r"(p2[3]) : "r"(s2a + i * 4096) : "memory");
                    asm volatile("ld.shared.v4.b32 {%0, %1, %2, %3}, [%4];" : "=r"(a[0]), "=r"(a[1]), "=r"(a[2]), "=r"(a[3]) : "r"(ga + i * 4096) : "memory");
#pragma unroll
                    for (int e = 0; e < 4; e++)
                        asm volatile("ld.shared.b32 %0, [%1];" : "=r"(x[e]) : "r"(xs + (e & 1) * 8 * 160 + (2 * i + (e >> 1)) * 16) : "memory");
#pragma unroll
                    for (int e = 0; e < 4; e++) {
                        const uint32_t sb = pack_bf16(bf_lo(p0[e]) + bf_lo(p1[e]) + bf_lo(p2[e]), bf_hi(p0[e]) + bf_hi(p1[e]) + bf_hi(p2[e]));
                        const uint32_t r = hmul2_bf16(sb, a[e]);
                        const uint32_t o = pack_bf16(bf_lo(x[e]) + bf_lo(r), bf_hi(x[e]) + bf_hi(r));
                        asm volatile("st.shared.b32 [%0], %1;" :: "r"(xs + (e & 1) * 8 * 160 + (2 * i + (e >> 1)) * 16), "r"(o) : "memory");
                    }
                }
            }
            TSTAMP(28);
            CSTAMP(8);
            asm volatile("fence.proxy.async.shared::cta;" ::: "memory");
            named_sync(5, 256);
            TSTAMP(29);
            CSTAMP(9);
            if (tid == 0) {
                asm volatile("cp.async.bulk.tensor.2d.global.shared::cta.bulk_group [%0, {%2, %3}], [%1];"
                             :: "l"(&tm_out), "r"(sbase + XS_OFF), "r"((g & 1) * 320 + kq * 80), "r"(t * 128) : "memory");
                asm volatile("cp.async.bulk.commit_group;" ::: "memory");
                asm volatile("cp.async.bulk.wait_group.read 0;" ::: "memory");
            }
            TSTAMP(6);
            CSTAMP(10);
        }
    }
}

typedef CUresult (*PFN_encodeTiled)(CUtensorMap*, CUtensorMapDataType, cuuint32_t, void*, const cuuint64_t*, const cuuint64_t*,
                                    const cuuint32_t*, const cuuint32_t*, CUtensorMapInterleave, CUtensorMapSwizzle,
                                    CUtensorMapL2promotion, CUtensorMapFloatOOBfill);

bool encode(PFN_encodeTiled fn, CUtensorMap* m, const void* base, int rank, const cuuint64_t* dims, const cuuint64_t* strides,
            const cuuint32_t* box) {
    cuuint32_t es[5] = {1, 1, 1, 1, 1};
    return fn(m, CU_TENSOR_MAP_DATA_TYPE_BFLOAT16, rank, const_cast<void*>(base), dims, strides, box, es,
              CU_TENSOR_MAP_INTERLEAVE_NONE, CU_TENSOR_MAP_SWIZZLE_128B, CU_TENSOR_MAP_L2_PROMOTION_L2_128B,
              CU_TENSOR_MAP_FLOAT_OOB_FILL_NONE) == CUDA_SUCCESS;
}
bool encode2d(PFN_encodeTiled fn, CUtensorMap* m, const void* base, uint64_t cols, uint64_t rows, uint32_t box_rows) {
    cuuint64_t dims[2] = {cols, rows};
    cuuint64_t strides[1] = {cols * 2};
    cuuint32_t box[2] = {64, box_rows};
    return encode(fn, m, base, 2, dims, strides, box);
}
bool encode_out(PFN_encodeTiled fn, CUtensorMap* m, void* base) {
    cuuint64_t dims[2] = {DM, S_LEN};
    cuuint64_t strides[1] = {DM * 2};
    cuuint32_t box[2] = {80, 128};
    cuuint32_t es[2] = {1, 1};
    return fn(m, CU_TENSOR_MAP_DATA_TYPE_BFLOAT16, 2, base, dims, strides, box, es, CU_TENSOR_MAP_INTERLEAVE_NONE,
              CU_TENSOR_MAP_SWIZZLE_NONE, CU_TENSOR_MAP_L2_PROMOTION_NONE, CU_TENSOR_MAP_FLOAT_OOB_FILL_NONE) == CUDA_SUCCESS;
}
bool encode_perm(PFN_encodeTiled fn, CUtensorMap* m, const void* base, uint64_t rows) {
    cuuint64_t dims[5] = {64, 2, rows / 8, 4, 10};
    cuuint64_t strides[4] = {DM * 2, 8 * DM * 2, 2 * DM * 2, 128};
    cuuint32_t box[5] = {64, 2, 4, 4, 5};
    return encode(fn, m, base, 5, dims, strides, box);
}

}

extern "C" void kernel_launch(void* const* d_in, const int* in_sizes, int n_in, void* d_out, int out_size) {
    (void)in_sizes; (void)n_in; (void)out_size;
    static PFN_encodeTiled enc = nullptr;
    static void* p_oq = nullptr;
    static void* p_h = nullptr;
    if (!enc) {
        void* p = nullptr;
        cudaDriverEntryPointQueryResult qr;
        if (cudaGetDriverEntryPoint("cuTensorMapEncodeTiled", &p, cudaEnableDefault, &qr) != cudaSuccess || !p) {
            fprintf(stderr, "cuTensorMapEncodeTiled not found\n");
            return;
        }
        enc = (PFN_encodeTiled)p;
        cudaGetSymbolAddress(&p_oq, g_oq);
        cudaGetSymbolAddress(&p_h, g_h);
        cudaFuncSetAttribute(fused_kernel, cudaFuncAttributeMaxDynamicSharedMemorySize, SMEM_BYTES);
    }
    const void* x = d_in[0];
    const void* kc = d_in[1];
    const void* vc = d_in[2];
    const void* wq = d_in[3];
    const void* wo = d_in[4];
    const void* w1 = d_in[6];
    const void* w3 = d_in[7];
    const void* w2 = d_in[8];
    CUtensorMap tm_w1, tm_w3, tm_wq, tm_k, tm_v, tm_wo, tm_w2, tm_o, tm_h, tm_x, tm_out, tm_xs;
    bool ok = encode2d(enc, &tm_w1, w1, FF, DM, 64) && encode2d(enc, &tm_w3, w3, FF, DM, 64) &&
              encode2d(enc, &tm_wq, wq, NH * DH, DM, 64) && encode2d(enc, &tm_k, kc, DH, (uint64_t)NH * SKV, 64) &&
              encode2d(enc, &tm_v, vc, DH, (uint64_t)NH * SKV, 64) && encode_perm(enc, &tm_wo, wo, NH * DH) &&
              encode_perm(enc, &tm_w2, w2, FF) && encode2d(enc, &tm_o, p_oq, NH * DH, S_LEN, 128) &&
              encode2d(enc, &tm_h, p_h, FF, S_LEN, 128) && encode2d(enc, &tm_x, x, DM, S_LEN, 128) && encode_out(enc, &tm_out, d_out) && encode_out(enc, &tm_xs, const_cast<void*>(x));
    if (!ok) { fprintf(stderr, "tensor map encode failed\n"); return; }
    Params prm;
    prm.x = (const __nv_bfloat16*)x;
    prm.out = (__nv_bfloat16*)d_out;
    cudaLaunchConfig_t cfg = {};
    cfg.gridDim = dim3(128);
    cfg.blockDim = dim3(384);
    cfg.dynamicSmemBytes = SMEM_BYTES;
    cfg.stream = cudaStreamPerThread;
    cudaLaunchAttribute at[1];
    at[0].id = cudaLaunchAttributeClusterDimension;
    at[0].val.clusterDim.x = 2; at[0].val.clusterDim.y = 1; at[0].val.clusterDim.z = 1;
    cfg.attrs = at;
    cfg.numAttrs = 1;
    cudaError_t e = cudaLaunchKernelEx(&cfg, fused_kernel, tm_w1, tm_w3, tm_wq, tm_k, tm_v, tm_wo, tm_w2, tm_o, tm_h, tm_x, tm_out, tm_xs, prm);
    if (e != cudaSuccess) fprintf(stderr, "launch failed: %s\n", cudaGetErrorString(e));
}
```

```cpp
#include <cuda_runtime.h>
#include <cuda_bf16.h>
#include <cuda.h>
#include <stdint.h>
#include <stdio.h>

namespace {

constexpr int S_LEN = 2048, DM = 640, NH = 32, DH = 128, SKV = 2048, WIN = 512, KOFF = SKV - WIN, FF = 1728;
constexpr int SLOT = 16384;
constexpr int OFF_RINGG = 10 * SLOT;
constexpr int OFF_BAR = 14 * SLOT;
constexpr int SMEM_BYTES = OFF_BAR + 1024 + 1024;
constexpr int ST3 = 57344;

constexpr int NP = 5;
enum { B_FULLG = 0, B_EMPTYG = 4, B_FULLA = 8, B_EMPTYA = 15, B_FULL3 = 22, B_EMPTY3 = 26, B_XNFREE = 30, B_PUB = 31, B_IN = 39, B_X = 42, B_XS = 52, B_FREE = 53, B_COUNT = 54 };

__device__ __align__(1024) __nv_bfloat16 g_oq[S_LEN * NH * DH];
__device__ __align__(1024) __nv_bfloat16 g_h[S_LEN * FF];
__device__ __align__(1024) uint4 g_part[32 * 4 * 4 * 5 * 256];
__device__ __align__(1024) unsigned g_cnt[16 * 128];

#define BAL 0
constexpr uint32_t PK_UNITS = 0x22344444u;
constexpr uint64_t PK_USTART = 0x191714100c080400ull, PK_NBLK = 0x1b1b181614151415ull;
__constant__ uint8_t c_blk[8][28] = {
    { 0,  1,  8,  9, 16,  2,  3, 10, 11, 18,  4,  5, 12, 13, 20,  6,  7, 14, 15, 22, 23,  0,  0,  0,  0,  0,  0,  0},
    { 0,  1,  8,  9, 16,  2,  3, 10, 11, 18,  4,  5, 12, 13, 20,  6,  7, 14, 15, 22,  0,  0,  0,  0,  0,  0,  0,  0},
    {17, 24, 25, 32, 33, 19, 26, 27, 34, 35, 21, 28, 29, 36, 37, 44, 30, 31, 38, 39, 46,  0,  0,  0,  0,  0,  0,  0},
    {17, 24, 25, 32, 33, 19, 26, 27, 34, 35, 21, 28, 29, 36, 37, 23, 30, 31, 38, 39,  0,  0,  0,  0,  0,  0,  0,  0},
    {40, 41, 48, 49, 56, 57, 42, 43, 50, 51, 58, 59, 45, 52, 53, 60, 61, 47, 54, 55, 62, 63,  0,  0,  0,  0,  0,  0},
    {40, 41, 48, 49, 56, 57, 42, 43, 50, 51, 58, 59, 44, 45, 52, 53, 60, 61, 46, 47, 54, 55, 62, 63,  0,  0,  0,  0},
    { 0,  1,  2,  3,  4,  5,  6,  7,  8,  9, 10, 11, 12, 13, 14, 15, 16, 17, 18, 19, 20, 21, 22, 23, 24, 25, 26,  0},
    { 0,  1,  2,  3,  4,  5,  6,  7,  8,  9, 10, 11, 12, 13, 14, 15, 16, 17, 18, 19, 20, 21, 22, 23, 24, 25, 26,  0},
};

__device__ __forceinline__ uint32_t smem_u32(const void* p) { return (uint32_t)__cvta_generic_to_shared(p); }
__device__ __forceinline__ void mbar_init(uint32_t bar, uint32_t count) {
    asm volatile("mbarrier.init.shared::cta.b64 [%0], %1;" :: "r"(bar), "r"(count));
}
__device__ __forceinline__ void mbar_expect_tx(uint32_t bar, uint32_t bytes) {
    asm volatile("mbarrier.arrive.expect_tx.shared::cta.b64 _, [%0], %1;" :: "r"(bar), "r"(bytes) : "memory");
}
__device__ __forceinline__ void mbar_arrive(uint32_t bar) {
    asm volatile("mbarrier.arrive.shared::cta.b64 _, [%0];" :: "r"(bar) : "memory");
}
__device__ __forceinline__ void mbar_arrive_cluster(uint32_t bar, uint32_t cta) {
    asm volatile("{\n.reg .b32 ra;\nmapa.shared::cluster.u32 ra, %0, %1;\nmbarrier.arrive.shared::cluster.b64 _, [ra];\n}"
                 :: "r"(bar), "r"(cta) : "memory");
}
__device__ __forceinline__ void mbar_wait(uint32_t bar, uint32_t parity, int code = 0) {
    (void)code;
    asm volatile("{\n.reg .pred p, q;\n.reg .u64 t0, t1;\n"
                 "mbarrier.try_wait.parity.shared::cta.b64 p, [%0], %1;\n"
                 "@p bra DONE;\n"
                 "mov.u64 t0, %%clock64;\n"
                 "LOOP:\n"
                 "mbarrier.try_wait.parity.shared::cta.b64 p, [%0], %1;\n"
                 "@p bra DONE;\n"
                 "mov.u64 t1, %%clock64;\n"
                 "sub.u64 t1, t1, t0;\n"
                 "setp.lt.u64 q, t1, 4000000000;\n"
                 "@q bra LOOP;\n"
                 "trap;\n"
                 "DONE:\n}"
                 :: "r"(bar), "r"(parity) : "memory");
}
__device__ __forceinline__ void mbar_wait_u(uint32_t bar, uint32_t parity) {
    asm volatile("{\n.reg .pred p, q;\n.reg .u64 t0, t1;\n"
                 "mbarrier.try_wait.parity.shared::cta.b64 p, [%0], %1;\n"
                 "vote.sync.all.pred p, p, 0xffffffff;\n"
                 "@p bra.uni DONE;\n"
                 "mov.u64 t0, %%clock64;\n"
                 "LOOP:\n"
                 "mbarrier.try_wait.parity.shared::cta.b64 p, [%0], %1;\n"
                 "vote.sync.all.pred p, p, 0xffffffff;\n"
                 "@p bra.uni DONE;\n"
                 "mov.u64 t1, %%clock64;\n"
                 "sub.u64 t1, t1, t0;\n"
                 "setp.lt.u64 q, t1, 4000000000;\n"
                 "vote.sync.any.pred q, q, 0xffffffff;\n"
                 "@q bra.uni LOOP;\n"
                 "trap;\n"
                 "DONE:\n}"
                 :: "r"(bar), "r"(parity) : "memory");
}
__device__ __forceinline__ void mbar_wait2(uint32_t b0, uint32_t p0, uint32_t b1, uint32_t p1) {
    asm volatile("{\n.reg .pred p, q;\n.reg .u64 t0, t1;\n"
                 "mbarrier.try_wait.parity.shared::cta.b64 p, [%0], %1;\n"
                 "mbarrier.try_wait.parity.shared::cta.b64 q, [%2], %3;\n"
                 "and.pred p, p, q;\n"
                 "vote.sync.all.pred p, p, 0xffffffff;\n"
                 "@p bra.uni DONE;\n"
                 "mov.u64 t0, %%clock64;\n"
                 "LOOP:\n"
                 "mbarrier.try_wait.parity.shared::cta.b64 p, [%0], %1;\n"
                 "mbarrier.try_wait.parity.shared::cta.b64 q, [%2], %3;\n"
                 "and.pred p, p, q;\n"
                 "vote.sync.all.pred p, p, 0xffffffff;\n"
                 "@p bra.uni DONE;\n"
                 "mov.u64 t1, %%clock64;\n"
                 "sub.u64 t1, t1, t0;\n"
                 "setp.lt.u64 q, t1, 4000000000;\n"
                 "vote.sync.any.pred q, q, 0xffffffff;\n"
                 "@q bra.uni LOOP;\n"
                 "trap;\n"
                 "DONE:\n}"
                 :: "r"(b0), "r"(p0), "r"(b1), "r"(p1) : "memory");
}
__device__ __forceinline__ uint32_t mbar_probe(uint32_t b0, uint32_t p0) {
    uint32_t ok;
    asm volatile("{\n.reg .pred p;\nmbarrier.test_wait.parity.shared::cta.b64 p, [%1], %2;\nselp.u32 %0, 1, 0, p;\n}"
                 : "=r"(ok) : "r"(b0), "r"(p0) : "memory");
    return ok;
}
__device__ __forceinline__ void mbar_wait4(uint32_t b0, uint32_t p0, uint32_t b1, uint32_t p1, uint32_t b2, uint32_t p2, uint32_t b3, uint32_t p3) {
    asm volatile("{\n.reg .pred p, q, r, s;\n.reg .u64 t0, t1;\n"
                 "mov.u64 t0, 0;\n"
                 "LOOP:\n"
                 "mbarrier.try_wait.parity.shared::cta.b64 p, [%0], %1;\n"
                 "mbarrier.try_wait.parity.shared::cta.b64 q, [%2], %3;\n"
                 "mbarrier.try_wait.parity.shared::cta.b64 r, [%4], %5;\n"
                 "mbarrier.try_wait.parity.shared::cta.b64 s, [%6], %7;\n"
                 "and.pred p, p, q;\nand.pred r, r, s;\nand.pred p, p, r;\n"
                 "vote.sync.all.pred p, p, 0xffffffff;\n"
                 "@p bra.uni DONE;\n"
                 "mov.u64 t1, %%clock64;\n"
                 "setp.eq.u64 q, t0, 0;\n"
                 "selp.u64 t0, t1, t0, q;\n"
                 "sub.u64 t1, t1, t0;\n"
                 "setp.lt.u64 q, t1, 4000000000;\n"
                 "vote.sync.any.pred q, q, 0xffffffff;\n"
                 "@q bra.uni LOOP;\n"
                 "trap;\n"
                 "DONE:\n}"
                 :: "r"(b0), "r"(p0), "r"(b1), "r"(p1), "r"(b2), "r"(p2), "r"(b3), "r"(p3) : "memory");
}
__device__ __forceinline__ uint32_t mbar_probe2(uint32_t b0, uint32_t p0, uint32_t b1, uint32_t p1) {
    uint32_t ok;
    asm volatile("{\n.reg .pred p, q;\n"
                 "mbarrier.test_wait.parity.shared::cta.b64 p, [%1], %2;\n"
                 "mbarrier.test_wait.parity.shared::cta.b64 q, [%3], %4;\n"
                 "and.pred p, p, q;\n"
                 "selp.u32 %0, 1, 0, p;\n}"
                 : "=r"(ok) : "r"(b0), "r"(p0), "r"(b1), "r"(p1) : "memory");
    return ok;
}
__device__ __forceinline__ uint32_t mapa_u32(uint32_t addr, uint32_t cta) {
    uint32_t r;
    asm("mapa.shared::cluster.u32 %0, %1, %2;" : "=r"(r) : "r"(addr), "r"(cta));
    return r;
}
__device__ __forceinline__ void mbar_arrive_remote(uint32_t cluster_addr) {
    asm volatile("mbarrier.arrive.shared::cluster.b64 _, [%0];" :: "r"(cluster_addr) : "memory");
}
__device__ __forceinline__ void mbar_arrive_remote_if(uint32_t cluster_addr, uint32_t flag) {
    asm volatile("{\n.reg .pred p;\nsetp.ne.u32 p, %1, 0;\n@p mbarrier.arrive.shared::cluster.b64 _, [%0];\n}"
                 :: "r"(cluster_addr), "r"(flag) : "memory");
}
__device__ __forceinline__ void mbar_arrive_if(uint32_t addr, uint32_t flag) {
    asm volatile("{\n.reg .pred p;\nsetp.ne.u32 p, %1, 0;\n@p mbarrier.arrive.shared::cta.b64 _, [%0];\n}"
                 :: "r"(addr), "r"(flag) : "memory");
}
__device__ __forceinline__ void mbar_arrive_warp(uint32_t addr, uint32_t lane_flag) {
    __syncwarp();
    asm volatile("{\n.reg .pred p;\nsetp.ne.u32 p, %1, 0;\n@p mbarrier.arrive.shared::cta.b64 _, [%0];\n}"
                 :: "r"(addr), "r"(lane_flag) : "memory");
}
__device__ __forceinline__ void tma_2d_mc(uint32_t dst, const CUtensorMap* m, int c0, int c1, uint32_t bar) {
    asm volatile("cp.async.bulk.tensor.2d.shared::cluster.global.mbarrier::complete_tx::bytes.multicast::cluster"
                 " [%0], [%1, {%3, %4}], [%2], %5;"
                 :: "r"(dst), "l"(m), "r"(bar), "r"(c0), "r"(c1), "h"((uint16_t)3) : "memory");
}
__device__ __forceinline__ void tma_2d(uint32_t dst, const CUtensorMap* m, int c0, int c1, uint32_t bar) {
    asm volatile("cp.async.bulk.tensor.2d.shared::cluster.global.mbarrier::complete_tx::bytes [%0], [%1, {%3, %4}], [%2];"
                 :: "r"(dst), "l"(m), "r"(bar), "r"(c0), "r"(c1) : "memory");
}
__device__ __forceinline__ void tma_5d_mc(uint32_t dst, const CUtensorMap* m, int c2, int c4, uint32_t bar) {
    asm volatile("cp.async.bulk.tensor.5d.shared::cluster.global.mbarrier::complete_tx::bytes.multicast::cluster"
                 " [%0], [%1, {%5, %5, %3, %5, %4}], [%2], %6;"
                 :: "r"(dst), "l"(m), "r"(bar), "r"(c2), "r"(c4), "r"(0), "h"((uint16_t)3) : "memory");
}
__device__ __forceinline__ void bulk_load(uint32_t dst, const void* src, uint32_t bytes, uint32_t bar) {
    asm volatile("cp.async.bulk.shared::cluster.global.mbarrier::complete_tx::bytes [%0], [%1], %2, [%3];"
                 :: "r"(dst), "l"(src), "r"(bytes), "r"(bar) : "memory");
}
__device__ __forceinline__ void bulk_store(void* dst, uint32_t src, uint32_t bytes) {
    asm volatile("cp.async.bulk.global.shared::cta.bulk_group [%0], [%1], %2;" :: "l"(dst), "r"(src), "r"(bytes) : "memory");
    asm volatile("cp.async.bulk.commit_group;" ::: "memory");
}
template <int N> __device__ __forceinline__ void bulk_wait() { asm volatile("cp.async.bulk.wait_group %0;" :: "n"(N) : "memory"); }
__device__ __forceinline__ void prefetch_2d(const CUtensorMap* m, int c0, int c1) {
    asm volatile("cp.async.bulk.prefetch.tensor.2d.L2.global [%0, {%1, %2}];" :: "l"(m), "r"(c0), "r"(c1) : "memory");
}
__device__ __forceinline__ void prefetch_5d(const CUtensorMap* m, int c2, int c4) {
    asm volatile("cp.async.bulk.prefetch.tensor.5d.L2.global [%0, {%3, %3, %1, %3, %2}];" :: "l"(m), "r"(c2), "r"(c4), "r"(0) : "memory");
}
__device__ __forceinline__ void cluster_sync() {
    asm volatile("barrier.cluster.arrive.release.aligned;\nbarrier.cluster.wait.acquire.aligned;" ::: "memory");
}
__device__ __forceinline__ void prefetch_tmap(const CUtensorMap* m) { asm volatile("prefetch.tensormap [%0];" :: "l"(m) : "memory"); }
__device__ __forceinline__ void cluster_arrive_relaxed() { asm volatile("barrier.cluster.arrive.relaxed.aligned;" ::: "memory"); }
__device__ __forceinline__ void cluster_wait() { asm volatile("barrier.cluster.wait.acquire.aligned;" ::: "memory"); }
__device__ __forceinline__ void mma_bf16(float (&d)[4], uint32_t a0, uint32_t a1, uint32_t a2, uint32_t a3, uint32_t b0, uint32_t b1) {
    asm volatile("mma.sync.aligned.m16n8k16.row.col.f32.bf16.bf16.f32 {%0, %1, %2, %3}, {%4, %5, %6, %7}, {%8, %9}, {%0, %1, %2, %3};"
                 : "+f"(d[0]), "+f"(d[1]), "+f"(d[2]), "+f"(d[3]) : "r"(a0), "r"(a1), "r"(a2), "r"(a3), "r"(b0), "r"(b1));
}
__device__ __forceinline__ uint32_t hsub2_bf16(uint32_t a, uint32_t b) { uint32_t r; asm("sub.rn.bf16x2 %0, %1, %2;" : "=r"(r) : "r"(a), "r"(b)); return r; }
__device__ __forceinline__ uint32_t hfma2_bf16(uint32_t a, uint32_t b, uint32_t c) { uint32_t r; asm("fma.rn.bf16x2 %0, %1, %2, %3;" : "=r"(r) : "r"(a), "r"(b), "r"(c)); return r; }
__device__ __forceinline__ uint32_t cluster_ctarank() { uint32_t r; asm volatile("mov.u32 %0, %%cluster_ctarank;" : "=r"(r)); return r; }
__device__ __forceinline__ void wgmma_fence() { asm volatile("wgmma.fence.sync.aligned;" ::: "memory"); }
__device__ __forceinline__ void wgmma_commit() { asm volatile("wgmma.commit_group.sync.aligned;" ::: "memory"); }
template <int N> __device__ __forceinline__ void wgmma_wait() { asm volatile("wgmma.wait_group.sync.aligned %0;" :: "n"(N) : "memory"); }
template <int N> __device__ __forceinline__ void fence_regs(float (&d)[N]) {
#pragma unroll
    for (int i = 0; i < N; i++) asm volatile("" : "+f"(d[i]) :: "memory");
}
template <int N> __device__ __forceinline__ void fence_regs(uint32_t (&d)[N]) {
#pragma unroll
    for (int i = 0; i < N; i++) asm volatile("" : "+r"(d[i]) :: "memory");
}
__device__ __forceinline__ void named_sync(int id, int n) { asm volatile("bar.sync %0, %1;" :: "r"(id), "r"(n) : "memory"); }
__device__ __forceinline__ void named_arrive(int id, int n) { asm volatile("bar.arrive %0, %1;" :: "r"(id), "r"(n) : "memory"); }
__device__ __forceinline__ uint32_t desc_lo(uint32_t addr, uint32_t lbo_bytes) {
    return ((addr & 0x3FFFF) >> 4) | ((lbo_bytes >> 4) << 16);
}
__device__ __forceinline__ uint32_t opaque(uint32_t v) { asm volatile("" : "+r"(v)); return v; }
__device__ __forceinline__ uint32_t pack_bf16(float lo, float hi) {
    uint32_t r;
    asm("cvt.rn.bf16x2.f32 %0, %1, %2;" : "=r"(r) : "f"(hi), "f"(lo));
    return r;
}
__device__ __forceinline__ float bf_lo(uint32_t v) { return __uint_as_float(v << 16); }
__device__ __forceinline__ float bf_hi(uint32_t v) { return __uint_as_float(v & 0xffff0000u); }
__device__ __forceinline__ float bf_round(float x) { return bf_lo(pack_bf16(x, 0.f)); }
__device__ __forceinline__ float ex2(float x) { float r; asm("ex2.approx.ftz.f32 %0, %1;" : "=f"(r) : "f"(x)); return r; }
__device__ __forceinline__ float rcp(float x) { float r; asm("rcp.approx.ftz.f32 %0, %1;" : "=f"(r) : "f"(x)); return r; }
__device__ __forceinline__ float silu_f(float x) { return x * rcp(1.0f + ex2(x * -1.4426950408889634f)); }
__device__ __forceinline__ uint32_t hmul2_bf16(uint32_t a, uint32_t b) {
    uint32_t r;
    asm("mul.rn.bf16x2 %0, %1, %2;" : "=r"(r) : "r"(a), "r"(b));
    return r;
}
__device__ __forceinline__ unsigned ld_acquire(const unsigned* p) {
    unsigned v;
    asm volatile("ld.acquire.gpu.global.u32 %0, [%1];" : "=r"(v) : "l"(p) : "memory");
    return v;
}
__device__ __forceinline__ void red_release(unsigned* p, unsigned v) {
    asm volatile("red.release.gpu.global.add.u32 [%0], %1;" :: "l"(p), "r"(v) : "memory");
}
__device__ __forceinline__ void wait_flag(const unsigned* p, unsigned target, int code) {
    (void)code;
    if ((int)(ld_acquire(p) - target) >= 0) return;
    long long t0 = clock64();
    while ((int)(ld_acquire(p) - target) < 0) {
        __nanosleep(40);
        if (clock64() - t0 > 4000000000ll) __trap();
    }
}

__device__ __forceinline__ void wgmma_ss_n128_tb(float (&d)[64], uint32_t da, uint32_t db, int scale_d) {
    asm volatile("{\n.reg .pred p;\n.reg .b64 da, db;\nsetp.ne.b32 p, %66, 0;\n"
        "mov.b64 da, {%64, 0x40000040};\nmov.b64 db, {%65, 0x40000040};\n"
        "wgmma.mma_async.sync.aligned.m64n128k16.f32.bf16.bf16 "
        "{%0, %1, %2, %3, %4, %5, %6, %7, %8, %9, %10, %11, %12, %13, %14, %15, "
        "%16, %17, %18, %19, %20, %21, %22, %23, %24, %25, %26, %27, %28, %29, %30, %31, "
        "%32, %33, %34, %35, %36, %37, %38, %39, %40, %41, %42, %43, %44, %45, %46, %47, "
        "%48, %49, %50, %51, %52, %53, %54, %55, %56, %57, %58, %59, %60, %61, %62, %63}, "
        "da, db, p, 1, 1, 0, 1;\n}"
        : "+f"(d[0]), "+f"(d[1]), "+f"(d[2]), "+f"(d[3]), "+f"(d[4]), "+f"(d[5]), "+f"(d[6]), "+f"(d[7]),
          "+f"(d[8]), "+f"(d[9]), "+f"(d[10]), "+f"(d[11]), "+f"(d[12]), "+f"(d[13]), "+f"(d[14]), "+f"(d[15]),
          "+f"(d[16]), "+f"(d[17]), "+f"(d[18]), "+f"(d[19]), "+f"(d[20]), "+f"(d[21]), "+f"(d[22]), "+f"(d[23]),
          "+f"(d[24]), "+f"(d[25]), "+f"(d[26]), "+f"(d[27]), "+f"(d[28]), "+f"(d[29]), "+f"(d[30]), "+f"(d[31]),
          "+f"(d[32]), "+f"(d[33]), "+f"(d[34]), "+f"(d[35]), "+f"(d[36]), "+f"(d[37]), "+f"(d[38]), "+f"(d[39]),
          "+f"(d[40]), "+f"(d[41]), "+f"(d[42]), "+f"(d[43]), "+f"(d[44]), "+f"(d[45]), "+f"(d[46]), "+f"(d[47]),
          "+f"(d[48]), "+f"(d[49]), "+f"(d[50]), "+f"(d[51]), "+f"(d[52]), "+f"(d[53]), "+f"(d[54]), "+f"(d[55]),
          "+f"(d[56]), "+f"(d[57]), "+f"(d[58]), "+f"(d[59]), "+f"(d[60]), "+f"(d[61]), "+f"(d[62]), "+f"(d[63])
        : "r"(da), "r"(db), "r"(scale_d));
}
__device__ __forceinline__ void wgmma_rs_n128_kb(float (&d)[64], uint32_t a0, uint32_t a1, uint32_t a2, uint32_t a3, uint32_t db, int scale_d) {
    asm volatile("{\n.reg .pred p;\n.reg .b64 da, db;\nsetp.ne.b32 p, %69, 0;\n"
        "mov.b64 db, {%68, 0x40000040};\n"
        "wgmma.mma_async.sync.aligned.m64n128k16.f32.bf16.bf16 "
        "{%0, %1, %2, %3, %4, %5, %6, %7, %8, %9, %10, %11, %12, %13, %14, %15, "
        "%16, %17, %18, %19, %20, %21, %22, %23, %24, %25, %26, %27, %28, %29, %30, %31, "
        "%32, %33, %34, %35, %36, %37, %38, %39, %40, %41, %42, %43, %44, %45, %46, %47, "
        "%48, %49, %50, %51, %52, %53, %54, %55, %56, %57, %58, %59, %60, %61, %62, %63}, "
        "{%64, %65, %66, %67}, db, p, 1, 1, 0;\n}"
        : "+f"(d[0]), "+f"(d[1]), "+f"(d[2]), "+f"(d[3]), "+f"(d[4]), "+f"(d[5]), "+f"(d[6]), "+f"(d[7]),
          "+f"(d[8]), "+f"(d[9]), "+f"(d[10]), "+f"(d[11]), "+f"(d[12]), "+f"(d[13]), "+f"(d[14]), "+f"(d[15]),
          "+f"(d[16]), "+f"(d[17]), "+f"(d[18]), "+f"(d[19]), "+f"(d[20]), "+f"(d[21]), "+f"(d[22]), "+f"(d[23]),
          "+f"(d[24]), "+f"(d[25]), "+f"(d[26]), "+f"(d[27]), "+f"(d[28]), "+f"(d[29]), "+f"(d[30]), "+f"(d[31]),
          "+f"(d[32]), "+f"(d[33]), "+f"(d[34]), "+f"(d[35]), "+f"(d[36]), "+f"(d[37]), "+f"(d[38]), "+f"(d[39]),
          "+f"(d[40]), "+f"(d[41]), "+f"(d[42]), "+f"(d[43]), "+f"(d[44]), "+f"(d[45]), "+f"(d[46]), "+f"(d[47]),
          "+f"(d[48]), "+f"(d[49]), "+f"(d[50]), "+f"(d[51]), "+f"(d[52]), "+f"(d[53]), "+f"(d[54]), "+f"(d[55]),
          "+f"(d[56]), "+f"(d[57]), "+f"(d[58]), "+f"(d[59]), "+f"(d[60]), "+f"(d[61]), "+f"(d[62]), "+f"(d[63])
        : "r"(a0), "r"(a1), "r"(a2), "r"(a3), "r"(db), "r"(scale_d));
}
__device__ __forceinline__ void wgmma_rs_n128_tb(float (&d)[64], uint32_t a0, uint32_t a1, uint32_t a2, uint32_t a3, uint32_t db, int scale_d) {
    asm volatile("{\n.reg .pred p;\n.reg .b64 da, db;\nsetp.ne.b32 p, %69, 0;\n"
        "mov.b64 db, {%68, 0x40000040};\n"
        "wgmma.mma_async.sync.aligned.m64n128k16.f32.bf16.bf16 "
        "{%0, %1, %2, %3, %4, %5, %6, %7, %8, %9, %10, %11, %12, %13, %14, %15, "
        "%16, %17, %18, %19, %20, %21, %22, %23, %24, %25, %26, %27, %28, %29, %30, %31, "
        "%32, %33, %34, %35, %36, %37, %38, %39, %40, %41, %42, %43, %44, %45, %46, %47, "
        "%48, %49, %50, %51, %52, %53, %54, %55, %56, %57, %58, %59, %60, %61, %62, %63}, "
        "{%64, %65, %66, %67}, db, p, 1, 1, 1;\n}"
        : "+f"(d[0]), "+f"(d[1]), "+f"(d[2]), "+f"(d[3]), "+f"(d[4]), "+f"(d[5]), "+f"(d[6]), "+f"(d[7]),
          "+f"(d[8]), "+f"(d[9]), "+f"(d[10]), "+f"(d[11]), "+f"(d[12]), "+f"(d[13]), "+f"(d[14]), "+f"(d[15]),
          "+f"(d[16]), "+f"(d[17]), "+f"(d[18]), "+f"(d[19]), "+f"(d[20]), "+f"(d[21]), "+f"(d[22]), "+f"(d[23]),
          "+f"(d[24]), "+f"(d[25]), "+f"(d[26]), "+f"(d[27]), "+f"(d[28]), "+f"(d[29]), "+f"(d[30]), "+f"(d[31]),
          "+f"(d[32]), "+f"(d[33]), "+f"(d[34]), "+f"(d[35]), "+f"(d[36]), "+f"(d[37]), "+f"(d[38]), "+f"(d[39]),
          "+f"(d[40]), "+f"(d[41]), "+f"(d[42]), "+f"(d[43]), "+f"(d[44]), "+f"(d[45]), "+f"(d[46]), "+f"(d[47]),
          "+f"(d[48]), "+f"(d[49]), "+f"(d[50]), "+f"(d[51]), "+f"(d[52]), "+f"(d[53]), "+f"(d[54]), "+f"(d[55]),
          "+f"(d[56]), "+f"(d[57]), "+f"(d[58]), "+f"(d[59]), "+f"(d[60]), "+f"(d[61]), "+f"(d[62]), "+f"(d[63])
        : "r"(a0), "r"(a1), "r"(a2), "r"(a3), "r"(db), "r"(scale_d));
}
__device__ __forceinline__ void wgmma_ss_n192_tb(float (&d)[96], uint32_t da, uint32_t db, int scale_d) {
    asm volatile("{\n.reg .pred p;\n.reg .b64 da, db;\nsetp.ne.b32 p, %98, 0;\n"
        "mov.b64 da, {%96, 0x40000040};\nmov.b64 db, {%97, 0x40000040};\n"
        "wgmma.mma_async.sync.aligned.m64n192k16.f32.bf16.bf16 "
        "{%0, %1, %2, %3, %4, %5, %6, %7, %8, %9, %10, %11, %12, %13, %14, %15, "
        "%16, %17, %18, %19, %20, %21, %22, %23, %24, %25, %26, %27, %28, %29, %30, %31, "
        "%32, %33, %34, %35, %36, %37, %38, %39, %40, %41, %42, %43, %44, %45, %46, %47, "
        "%48, %49, %50, %51, %52, %53, %54, %55, %56, %57, %58, %59, %60, %61, %62, %63, "
        "%64, %65, %66, %67, %68, %69, %70, %71, %72, %73, %74, %75, %76, %77, %78, %79, "
        "%80, %81, %82, %83, %84, %85, %86, %87, %88, %89, %90, %91, %92, %93, %94, %95}, "
        "da, db, p, 1, 1, 0, 1;\n}"
        : "+f"(d[0]), "+f"(d[1]), "+f"(d[2]), "+f"(d[3]), "+f"(d[4]), "+f"(d[5]), "+f"(d[6]), "+f"(d[7]),
          "+f"(d[8]), "+f"(d[9]), "+f"(d[10]), "+f"(d[11]), "+f"(d[12]), "+f"(d[13]), "+f"(d[14]), "+f"(d[15]),
          "+f"(d[16]), "+f"(d[17]), "+f"(d[18]), "+f"(d[19]), "+f"(d[20]), "+f"(d[21]), "+f"(d[22]), "+f"(d[23]),
          "+f"(d[24]), "+f"(d[25]), "+f"(d[26]), "+f"(d[27]), "+f"(d[28]), "+f"(d[29]), "+f"(d[30]), "+f"(d[31]),
          "+f"(d[32]), "+f"(d[33]), "+f"(d[34]), "+f"(d[35]), "+f"(d[36]), "+f"(d[37]), "+f"(d[38]), "+f"(d[39]),
          "+f"(d[40]), "+f"(d[41]), "+f"(d[42]), "+f"(d[43]), "+f"(d[44]), "+f"(d[45]), "+f"(d[46]), "+f"(d[47]),
          "+f"(d[48]), "+f"(d[49]), "+f"(d[50]), "+f"(d[51]), "+f"(d[52]), "+f"(d[53]), "+f"(d[54]), "+f"(d[55]),
          "+f"(d[56]), "+f"(d[57]), "+f"(d[58]), "+f"(d[59]), "+f"(d[60]), "+f"(d[61]), "+f"(d[62]), "+f"(d[63]),
          "+f"(d[64]), "+f"(d[65]), "+f"(d[66]), "+f"(d[67]), "+f"(d[68]), "+f"(d[69]), "+f"(d[70]), "+f"(d[71]),
          "+f"(d[72]), "+f"(d[73]), "+f"(d[74]), "+f"(d[75]), "+f"(d[76]), "+f"(d[77]), "+f"(d[78]), "+f"(d[79]),
          "+f"(d[80]), "+f"(d[81]), "+f"(d[82]), "+f"(d[83]), "+f"(d[84]), "+f"(d[85]), "+f"(d[86]), "+f"(d[87]),
          "+f"(d[88]), "+f"(d[89]), "+f"(d[90]), "+f"(d[91]), "+f"(d[92]), "+f"(d[93]), "+f"(d[94]), "+f"(d[95])
        : "r"(da), "r"(db), "r"(scale_d));
}

#define TSTAMP(i)
#define TSTAMP1(i)
#define TSTAMP_T(i, T)
#define CSTAMP(i)
#define ISTAMP(i)
#define FWRAP(k, stmt) do { stmt; } while (0)

template <int V> struct IC { static constexpr int value = V; };
template <int B, int E, class F> __device__ __forceinline__ void static_for(F&& f) {
    if constexpr (B < E) { f(IC<B>{}); static_for<B + 1, E>(f); }
}

constexpr float QSCALE = 0.08838834764831845f * 1.4426950408889634f;
#define G_PBASE0 1
#define G_PSTEP 1
constexpr int PSLAB = 5 * 256 * 16;
constexpr int XS_OFF = 7 * PSLAB;

struct Params {
    const __nv_bfloat16* x;
    __nv_bfloat16* out;
};

__device__ __forceinline__ void store_tile128(__nv_bfloat16* rowp  , size_t row8_stride,
                                              const float (&a)[64], float s0, float s1) {
#pragma unroll
    for (int m = 0; m < 4; m++) {
        uint4 v0, v1;
        v0.x = pack_bf16(a[16 * m + 0] * s0, a[16 * m + 1] * s0);
        v0.y = pack_bf16(a[16 * m + 4] * s0, a[16 * m + 5] * s0);
        v0.z = pack_bf16(a[16 * m + 8] * s0, a[16 * m + 9] * s0);
        v0.w = pack_bf16(a[16 * m + 12] * s0, a[16 * m + 13] * s0);
        v1.x = pack_bf16(a[16 * m + 2] * s1, a[16 * m + 3] * s1);
        v1.y = pack_bf16(a[16 * m + 6] * s1, a[16 * m + 7] * s1);
        v1.z = pack_bf16(a[16 * m + 10] * s1, a[16 * m + 11] * s1);
        v1.w = pack_bf16(a[16 * m + 14] * s1, a[16 * m + 15] * s1);
        *reinterpret_cast<uint4*>(rowp + 32 * m) = v0;
        *reinterpret_cast<uint4*>(rowp + row8_stride + 32 * m) = v1;
    }
}

template <int PIECE>
__device__ __forceinline__ void g_epi_piece(const float (&a)[64], int type, __nv_bfloat16* dst, int row8_stride, float rs0, float rs1) {
    asm volatile("" : "+f"(rs0), "+f"(rs1));
    if (type == 1) {
        constexpr int m = PIECE >> 1, rh = PIECE & 1;
        const float cexp = (rh ? rs1 : rs0) * -1.4426950408889634f;
        uint32_t o[4];
#pragma unroll
        for (int jj = 0; jj < 4; jj++) {
            const int gi = 16 * m + 4 * jj + 2 * rh;
            const uint32_t sg = pack_bf16(rcp(1.0f + ex2(a[gi] * cexp)), rcp(1.0f + ex2(a[gi + 1] * cexp)));
            o[jj] = hmul2_bf16(hmul2_bf16(pack_bf16(a[gi], a[gi + 1]), sg), pack_bf16(a[32 + gi], a[32 + gi + 1]));
        }
        *reinterpret_cast<uint4*>(dst + rh * row8_stride + 32 * m) = make_uint4(o[0], o[1], o[2], o[3]);
    } else if (type == 2) {
        constexpr int m = PIECE;
        uint4 v0, v1;
        rs0 *= QSCALE; rs1 *= QSCALE;
        v0.x = pack_bf16(a[16 * m + 0] * rs0, a[16 * m + 1] * rs0);
        v0.y = pack_bf16(a[16 * m + 2] * rs1, a[16 * m + 3] * rs1);
        v0.z = pack_bf16(a[16 * m + 4] * rs0, a[16 * m + 5] * rs0);
        v0.w = pack_bf16(a[16 * m + 6] * rs1, a[16 * m + 7] * rs1);
        v1.x = pack_bf16(a[16 * m + 8] * rs0, a[16 * m + 9] * rs0);
        v1.y = pack_bf16(a[16 * m + 10] * rs1, a[16 * m + 11] * rs1);
        v1.z = pack_bf16(a[16 * m + 12] * rs0, a[16 * m + 13] * rs0);
        v1.w = pack_bf16(a[16 * m + 14] * rs1, a[16 * m + 15] * rs1);
        *reinterpret_cast<uint4*>(dst + 32 * m) = v0;
        *reinterpret_cast<uint4*>(dst + row8_stride + 32 * m) = v1;
    }
}

struct GCtx {
    uint32_t a_lo, b_lo;
    uint32_t bars;
    int sg;
    float rs0, rs1;
    uint32_t lane0, ready;
    int pbase;
    uint32_t rbars, el;
};

__device__ __forceinline__ void g_stage(float (&acc)[64], GCtx& c, int kb, int accumulate) {
    const int s = c.sg & 3;
    if (!__all_sync(0xffffffffu, c.ready)) {
        mbar_wait_u(c.bars + (B_FULLG + s) * 8, (c.sg >> 2) & 1);
    }
    const uint32_t da = c.a_lo + kb * (SLOT >> 4);
    const uint32_t db = c.b_lo + s * (SLOT >> 4);
    wgmma_fence();
#pragma unroll
    for (int kk = 0; kk < 4; kk++)
        wgmma_ss_n128_tb(acc, da + kk * 2, db + kk * 128, kk != 0 ? 1 : accumulate);
    wgmma_commit();
    c.sg++;
    c.ready = mbar_probe(c.bars + (B_FULLG + (c.sg & 3)) * 8, (c.sg >> 2) & 1);
    wgmma_wait<1>();
    mbar_arrive_remote_if(c.rbars + (B_EMPTYG + ((c.sg - 2) & 3)) * 8, c.sg > 1 ? c.el : 0u);
}
__device__ __forceinline__ void g_tile(float (&acc)[64], float (&prev)[64], int ptype, __nv_bfloat16* pdst, int pstride,
                                       GCtx& c, uint32_t pub_bar) {
    g_stage(acc, c, 0, 0);
    fence_regs(prev);
#pragma unroll 1
    for (int kb = 1; kb < 10; kb++) {
        g_stage(acc, c, kb, 1);
        const int pc = ((kb - c.pbase) & 1) ? -1 : (kb - c.pbase) >> 1;
        if (pc == 0) g_epi_piece<0>(prev, ptype, pdst, pstride, c.rs0, c.rs1);
        else if (pc == 1) g_epi_piece<1>(prev, ptype, pdst, pstride, c.rs0, c.rs1);
        else if (pc == 2) g_epi_piece<2>(prev, ptype, pdst, pstride, c.rs0, c.rs1);
        else if (pc == 3) {
            g_epi_piece<3>(prev, ptype, pdst, pstride, c.rs0, c.rs1);
            mbar_arrive_warp(pub_bar, pub_bar && c.lane0);
        }
    }
}

__global__ void __launch_bounds__(384, 1)
fused_kernel(const __grid_constant__ CUtensorMap tm_w1, const __grid_constant__ CUtensorMap tm_w3,
             const __grid_constant__ CUtensorMap tm_wq, const __grid_constant__ CUtensorMap tm_k,
             const __grid_constant__ CUtensorMap tm_v, const __grid_constant__ CUtensorMap tm_wo,
             const __grid_constant__ CUtensorMap tm_w2, const __grid_constant__ CUtensorMap tm_o,
             const __grid_constant__ CUtensorMap tm_h, const __grid_constant__ CUtensorMap tm_x,
             const __grid_constant__ CUtensorMap tm_out, const __grid_constant__ CUtensorMap tm_xs, const Params prm) {
    extern __shared__ __align__(1024) uint8_t smem_raw[];
    const uint32_t sbase = (smem_u32(smem_raw) + 1023) & ~1023u;
    const uint32_t bars = sbase + OFF_BAR;
    const int tid = threadIdx.x;
    const int warp = __shfl_sync(0xffffffffu, tid >> 5, 0);
    const int wg = warp >> 2;
    const int lane = tid & 31;
    const uint32_t rank = cluster_ctarank();
    const int cl = blockIdx.x >> 1;
    const int g = cl & 7;
    const int t = (cl >> 3) * 2 + (int)rank;
    const int nunits = (PK_UNITS >> (4 * g)) & 15;
    const int ntiles = nunits + 4;
    const int ustart = (int)((PK_USTART >> (8 * g)) & 255);
    const int nblk = (int)((PK_NBLK >> (8 * g)) & 255);
    unsigned* cnt = g_cnt + t * 128;

    TSTAMP(0);
    if (tid == 0) {
        for (int i = 0; i < 10; i++) mbar_init(bars + (B_X + i) * 8, 1);
        asm volatile("fence.mbarrier_init.release.cluster;" ::: "memory");
        for (int i = 0; i < 10; i++) {
            mbar_expect_tx(bars + (B_X + i) * 8, SLOT);
            tma_2d(sbase + i * SLOT, &tm_x, i * 64, t * 128, bars + (B_X + i) * 8);
        }
        TSTAMP(17);
    } else if (tid == 64) {
        for (int i = 0; i < 4; i++) { mbar_init(bars + (B_FULLG + i) * 8, 1); mbar_init(bars + (B_EMPTYG + i) * 8, 4); }
        for (int i = 0; i < NP + 2; i++) { mbar_init(bars + (B_FULLA + i) * 8, 1); mbar_init(bars + (B_EMPTYA + i) * 8, 4); }
        for (int i = 0; i < 4; i++) { mbar_init(bars + (B_FULL3 + i) * 8, 1); mbar_init(bars + (B_EMPTY3 + i) * 8, 4); }
        mbar_init(bars + B_XNFREE * 8, 4);
        for (int i = 0; i < 8; i++) mbar_init(bars + (B_PUB + i) * 8, 8);
        for (int i = 0; i < 3; i++) mbar_init(bars + (B_IN + i) * 8, 1);
        mbar_init(bars + B_XS * 8, 1);
        mbar_init(bars + B_FREE * 8, 1);
        asm volatile("fence.mbarrier_init.release.cluster;" ::: "memory");
    } else if (tid == 32) {
        prefetch_tmap(&tm_w1); prefetch_tmap(&tm_w3); prefetch_tmap(&tm_wq); prefetch_tmap(&tm_k); prefetch_tmap(&tm_v);
        prefetch_tmap(&tm_wo); prefetch_tmap(&tm_w2); prefetch_tmap(&tm_o); prefetch_tmap(&tm_h);
    }
    __syncthreads();
    cluster_arrive_relaxed();

    if (wg == 2) {
        asm volatile("setmaxnreg.dec.sync.aligned.u32 40;");
        cluster_wait();
        const unsigned epoch = (*(volatile unsigned*)cnt) >> 3;
        auto recv_partial = [&](int d) {
            const int nh = g & 1, kq = g >> 1;
            const int src = d < kq ? d : d + 1;
            wait_flag(cnt + 64 + nh * 16 + kq * 4 + src, epoch + 1, 22);
            TSTAMP1(22 + d);
            asm volatile("fence.proxy.async;" ::: "memory");
            mbar_expect_tx(bars + (B_IN + d) * 8, PSLAB);
            bulk_load(sbase + (4 + d) * PSLAB, g_part + (size_t)(((t * 2 + nh) * 4 + src) * 4 + kq) * (PSLAB / 16), PSLAB, bars + (B_IN + d) * 8);
        };
        if (warp == 8 && lane == 0) {
            const int nG = 10 * ntiles;
            auto coords = [&](int s, const CUtensorMap*& m, int& c0, int& c1) {
                if (s < nG) {
                    const int tile = s / 10, kb = s - tile * 10;
                    if (tile < nunits) { m = rank ? &tm_w3 : &tm_w1; c0 = (ustart + tile) * 64; }
                    else { m = &tm_wq; c0 = (4 * g + ((tile - nunits + 1) & 3)) * 128 + rank * 64; }
                    c1 = kb * 64;
                } else {
                    const int n = s - nG;
                    int isv, it, half;
                    if (n < 2) { isv = 0; it = 0; half = n; }
                    else if (n >= 62) { isv = 1; it = 15; half = n - 62; }
                    else { const int q = (n - 2) >> 2, r = (n - 2) & 3; isv = r >> 1; it = q + 1 - isv; half = r & 1; }
                    const int kv0 = (4 * g + (it >> 2)) * SKV + KOFF + (it & 3) * 128;
                    if (isv) { m = &tm_v; c0 = rank * 64; c1 = kv0 + half * 64; }
                    else { m = &tm_k; c0 = half * 64; c1 = kv0 + rank * 64; }
                }
            };
            const int nh = g & 1, kq = g >> 1;
            const CUtensorMap* mb = (kq == 3) ? &tm_w2 : &tm_wo;
            const int pidx = cl >> 3;
            auto prefetch = [&](int s) {
                if ((s & 7) != pidx) return;
                if (s < nG + 64) {
                    const CUtensorMap* m; int c0, c1;
                    coords(s, m, c0, c1);
                    prefetch_2d(m, c0, c1);
                } else if (s - (nG + 64) < nblk) {
                    prefetch_5d(mb, c_blk[g][s - (nG + 64)] * 8 + rank * 4, nh * 5);
                }
            };
#define PF_DIST 12
            mbar_wait(bars + (B_X + 5) * 8, 0, 9);
            for (int s = 4; s < PF_DIST; s++) prefetch(s);
            int sg = 0;
            for (; sg < nG; sg++) {
                const CUtensorMap* m; int c0, c1;
                coords(sg, m, c0, c1);
                const int s = sg & 3;
                mbar_wait(bars + (B_EMPTYG + s) * 8, ((sg >> 2) & 1) ^ 1, 10);
                mbar_expect_tx(bars + (B_FULLG + s) * 8, SLOT);
                tma_2d_mc(sbase + OFF_RINGG + s * SLOT + rank * 8192, m, c0, c1, bars + (B_FULLG + s) * 8);
                prefetch(sg + PF_DIST);
            }
            int sa = 0, pa = 0;
            for (int T = 0; T < 32; T++) {
                uint32_t dst, fb;
                if (T < 2) {
                    for (int v = 0; v < 2; v++) mbar_wait(bars + (B_EMPTYG + ((sg + v) & 3)) * 8, (((sg + v) >> 2) & 1) ^ 1, 11);
                    dst = sbase + OFF_RINGG + (sg & 3) * SLOT; fb = bars + (B_FULLA + NP + T) * 8;
                    sg += 2;
                } else {
                    if (T == 2) mbar_wait(bars + B_XNFREE * 8, 0, 12);
                    if (T >= 2 + NP) mbar_wait(bars + (B_EMPTYA + sa) * 8, pa ^ 1, 13);
                    dst = sbase + sa * 2 * SLOT; fb = bars + (B_FULLA + sa) * 8;
                    if (++sa == NP) { sa = 0; pa ^= 1; }
                }
                mbar_expect_tx(fb, 2 * SLOT);
                for (int v = 0; v < 2; v++) {
                    const CUtensorMap* m; int c0, c1;
                    coords(nG + 2 * T + v, m, c0, c1);
                    tma_2d_mc(dst + v * SLOT + rank * 8192, m, c0, c1, fb);
                    prefetch(nG + 2 * T + v + PF_DIST);
                }
            }
            const CUtensorMap* ma = (kq == 3) ? &tm_h : &tm_o;
            int round_ok = -1;
            for (int i = 0; i < nblk; i++) {
                const int st = i & 3;
                if (i == 0) { mbar_wait(bars + (B_EMPTYA + NP) * 8, 0, 14); mbar_wait(bars + (B_EMPTYA + NP + 1) * 8, 0, 14); }
                else if (i == 1) { mbar_wait(bars + (B_EMPTYA + 0) * 8, pa ^ 1, 15); mbar_wait(bars + (B_EMPTYA + 1) * 8, pa ^ 1, 15); }
                else if (i == 2) { mbar_wait(bars + (B_EMPTYA + 2) * 8, pa ^ 1, 15); mbar_wait(bars + (B_EMPTYA + 3) * 8, pa ^ 1, 15); }
                else if (i == 3) mbar_wait(bars + (B_EMPTYA + 4) * 8, pa ^ 1, 15);
                else mbar_wait(bars + (B_EMPTY3 + st) * 8, ((i >> 2) & 1) ^ 1, 18);
                const int b = c_blk[g][i];
                const int round = (kq == 3) ? 0 : ((b >> 1) & 3);
                if (round != round_ok) {
                    if (kq == 3) wait_flag(cnt, (epoch + 1) * 8, 19);
                    else wait_flag(cnt + 8 + round * 8, (epoch + 1) * 8, 20);
                    asm volatile("fence.proxy.async;" ::: "memory");
                    round_ok = round;
                }
                const uint32_t base = sbase + ((st + 3) & 3) * ST3;
                const uint32_t fb = bars + (B_FULL3 + st) * 8;
                mbar_expect_tx(fb, ST3);
                tma_5d_mc(base + SLOT + rank * 20480, mb, b * 8 + rank * 4, nh * 5, fb);
                tma_2d(base, ma, b * 64, t * 128, fb);
                prefetch(nG + 64 + i + PF_DIST);
            }
            for (int i = nblk; i < nblk + 4; i++)
                mbar_wait(bars + (B_EMPTY3 + (i & 3)) * 8, ((i >> 2) & 1) ^ 1, 21);
            mbar_arrive(bars + B_FREE * 8);
            mbar_expect_tx(bars + B_XS * 8, PSLAB);
            tma_2d(sbase + XS_OFF, &tm_xs, nh * 320 + kq * 80, t * 128, bars + B_XS * 8);
            recv_partial(0);
        } else if (warp >= 10) {
            if (warp == 10) {
                for (int it = 0; it <= 16; it++) {
                    if (it < 2) mbar_wait_u(bars + (B_FULLA + NP + it) * 8, 0);
                    else if (it < 16) { const int m = 2 * it - 3; mbar_wait_u(bars + (B_FULLA + m % NP) * 8, (m / NP) & 1); }
                    if (it > 0) { const int m = it < 16 ? 2 * it - 2 : 29; mbar_wait_u(bars + (B_FULLA + m % NP) * 8, (m / NP) & 1); }
                    named_sync(1, 288);
                    named_sync(2, 288);
                }
            }
            if (lane == 0) {
                mbar_wait(bars + B_FREE * 8, 0, 21);
                recv_partial(warp - 9);
            }
        } else if (warp == 9 && lane == 0) {
            for (int ev = 0; ev < 5; ev++) {
                mbar_wait(bars + (B_PUB + ev) * 8, 0, 30);
                asm volatile("fence.proxy.async;" ::: "memory");
                __threadfence();
                red_release(ev == 0 ? cnt : cnt + 8 * ev, 1);
            }
            {
                const int nh = g & 1, kq = g >> 1;
                mbar_wait(bars + (B_PUB + 5) * 8, 0, 31);
                TSTAMP1(16);
                unsigned* fl = cnt + 64 + nh * 16 + kq;
                asm volatile("fence.proxy.async;" ::: "memory");
                asm volatile("fence.acq_rel.gpu;" ::: "memory");
                TSTAMP1(20);
                for (int d = 1; d < 4; d++)
                    asm volatile("red.relaxed.gpu.global.add.u32 [%0], %1;" :: "l"(fl + ((kq + d) & 3) * 4), "r"(1u) : "memory");
                TSTAMP1(21);
            }
        }
    } else {
        asm volatile("setmaxnreg.inc.sync.aligned.u32 232;");
        TSTAMP(7);
        const int wl = warp & 3;
        const int q4 = lane & 3;
        const uint32_t el = ((tid & 127) == 0 || (tid & 127) == 32) ? 1u : 0u;
        const uint32_t rbars = mapa_u32(bars, (tid & 127) == 32 ? 1u : 0u);
        const int row0 = t * 128 + wg * 64 + wl * 16 + (lane >> 2);

        float rs0, rs1;
        GCtx c;
        uint32_t qf[32];
        {
            float accA[64], accB[64];
            const int g8 = lane >> 2;
            const int ra = wg * 64 + wl * 16 + g8;
            uint32_t xa[80], xb[80];
            float sm[2][4] = {{0.f, 0.f, 0.f, 0.f}, {0.f, 0.f, 0.f, 0.f}};
            float ga[2][4] = {{0.f, 0.f, 0.f, 0.f}, {0.f, 0.f, 0.f, 0.f}}, gb[2][4] = {{0.f, 0.f, 0.f, 0.f}, {0.f, 0.f, 0.f, 0.f}};
            uint32_t sha = 0, shb = 0;
#pragma unroll
            for (int m = 0; m < 10; m++) {
                mbar_wait_u(bars + (B_X + m) * 8, 0);
                if (m == 0) TSTAMP(13);
                if (m == 2) TSTAMP(14);
                if (m == 5) TSTAMP(15);
                if (m == 9) TSTAMP(8);
#pragma unroll
                for (int ii = 0; ii < 2; ii++) {
                    const int i = 2 * m + ii;
                    const int c = q4 + 4 * (i ^ (g8 & 1));
                    const uint32_t src = sbase + m * SLOT + ra * 128 + (((c & 7) ^ (ra & 7)) << 4);
                    asm volatile("ld.shared.v4.b32 {%0, %1, %2, %3}, [%4];" : "=r"(xa[4 * i]), "=r"(xa[4 * i + 1]), "=r"(xa[4 * i + 2]), "=r"(xa[4 * i + 3]) : "r"(src) : "memory");
                    asm volatile("ld.shared.v4.b32 {%0, %1, %2, %3}, [%4];" : "=r"(xb[4 * i]), "=r"(xb[4 * i + 1]), "=r"(xb[4 * i + 2]), "=r"(xb[4 * i + 3]) : "r"(src + 8 * 128) : "memory");
                }
                if (m == 0) {
                    const uint32_t ea = (g8 & 1) ? xa[4] : xa[0], eb = (g8 & 1) ? xb[4] : xb[0];
                    sha = __shfl_sync(0xffffffffu, ea, lane & ~3); shb = __shfl_sync(0xffffffffu, eb, lane & ~3);
                    sha = __byte_perm(sha, sha, 0x1010); shb = __byte_perm(shb, shb, 0x1010);
                }
#pragma unroll
                for (int u = 0; u < 4; u++) {
                    const int e = 8 * m + 2 * u;
                    const uint32_t a0 = hsub2_bf16(xa[e], sha), a2 = hsub2_bf16(xa[e + 1], sha);
                    const uint32_t a1 = hsub2_bf16(xb[e], shb), a3 = hsub2_bf16(xb[e + 1], shb);
                    mma_bf16(sm[u & 1], a0, a1, a2, a3, 0x3F803F80u, 0x3F803F80u);
                    mma_bf16(ga[u & 1], a0, a1, a2, a3, a0, a2);
                    mma_bf16(gb[u & 1], a0, a1, a2, a3, a1, a3);
                }
            }
            TSTAMP(9);
            const float ea1 = (sm[0][0] + sm[1][0]) * (1.0f / DM), eb1 = (sm[0][2] + sm[1][2]) * (1.0f / DM);
            const float mean_a = bf_lo(sha) + ea1, mean_b = bf_lo(shb) + eb1;
            const uint32_t mab = pack_bf16(mean_a, mean_b);
            const uint32_t ma2 = __byte_perm(mab, mab, 0x1010), mb2 = __byte_perm(mab, mab, 0x3232);
            const int dl = 4 * g8 + (g8 >> 1);
            const float sqa = __shfl_sync(0xffffffffu, (g8 & 1) ? ga[0][1] + ga[1][1] : ga[0][0] + ga[1][0], dl);
            const float sqb = __shfl_sync(0xffffffffu, (g8 & 1) ? gb[0][3] + gb[1][3] : gb[0][2] + gb[1][2], dl);
            TSTAMP(10);
            const float var_a = bf_round(fmaxf(sqa * (1.0f / DM) - ea1 * ea1, 0.f));
            const float var_b = bf_round(fmaxf(sqb * (1.0f / DM) - eb1 * eb1, 0.f));
            const float inv_a = 1.0f / bf_round(sqrtf(bf_round(var_a + 1e-5f)));
            const float inv_b = 1.0f / bf_round(sqrtf(bf_round(var_b + 1e-5f)));
            rs0 = inv_a; rs1 = inv_b;
            auto centre = [&](auto M_) {
#pragma unroll
                for (int ii = 0; ii < 2; ii++) {
                    constexpr int m = decltype(M_)::value;
                    const int i = 2 * m + ii;
                    uint32_t oa[4], ob[4];
#pragma unroll
                    for (int e = 0; e < 4; e++) {
                        oa[e] = hsub2_bf16(xa[4 * i + e], ma2);
                        ob[e] = hsub2_bf16(xb[4 * i + e], mb2);
                    }
                    const int cc = q4 + 4 * (i ^ (g8 & 1));
                    const uint32_t dst = sbase + m * SLOT + ra * 128 + (((cc & 7) ^ (ra & 7)) << 4);
                    asm volatile("st.shared.v4.b32 [%0], {%1, %2, %3, %4};" :: "r"(dst), "r"(oa[0]), "r"(oa[1]), "r"(oa[2]), "r"(oa[3]) : "memory");
                    asm volatile("st.shared.v4.b32 [%0], {%1, %2, %3, %4};" :: "r"(dst + 8 * 128), "r"(ob[0]), "r"(ob[1]), "r"(ob[2]), "r"(ob[3]) : "memory");
                }
            };
            static_for<0, 4>([&](auto M_) { centre(M_); });
            TSTAMP(11);
            asm volatile("fence.proxy.async.shared::cta;" ::: "memory");
            named_sync(3 + wg, 128);
            TSTAMP(12);
            cluster_wait();
            TSTAMP(1);
            CSTAMP(14);
            c.a_lo = desc_lo(sbase + wg * 8192, 16); c.b_lo = desc_lo(sbase + OFF_RINGG, 8192); c.bars = bars; c.sg = 0; c.rbars = rbars; c.el = el;
            c.rs0 = rs0; c.rs1 = rs1; c.lane0 = lane == 0; c.ready = 0; c.pbase = G_PBASE0 + G_PSTEP * wg;
            g_stage(accA, c, 0, 0);
            centre(IC<4>{}); centre(IC<5>{});
            g_stage(accA, c, 1, 1);
            centre(IC<6>{}); centre(IC<7>{});
            g_stage(accA, c, 2, 1);
            centre(IC<8>{}); centre(IC<9>{});
            asm volatile("fence.proxy.async.shared::cta;" ::: "memory");
            g_stage(accA, c, 3, 1);
            named_sync(3 + wg, 128);
#pragma unroll 1
            for (int kb = 4; kb < 10; kb++) g_stage(accA, c, kb, 1);
            __nv_bfloat16* const hrow = g_h + (size_t)row0 * FF + 8 * q4;
            __nv_bfloat16* const qrow = g_oq + (size_t)row0 * (NH * DH) + 8 * q4;
            auto epi_type = [&](int i) { return i < nunits ? 1 : 2; };
            auto epi_dst = [&](int i) {
                return i < nunits ? hrow + (ustart + i) * 64 : qrow + (4 * g + ((i - nunits + 1) & 3)) * 128;
            };
            auto epi_stride = [&](int i) { return i < nunits ? 8 * FF : 8 * NH * DH; };
            auto epi_pub = [&](int i) { return (i == nunits - 1) ? bars + B_PUB * 8 : 0u; };
            if (ntiles & 1) {
                wgmma_wait<0>();
                fence_regs(accA);
#pragma unroll
                for (int i = 0; i < 64; i++) accB[i] = accA[i];
            } else {
#pragma unroll
                for (int i = 0; i < 64; i++) asm volatile("" : "=f"(accB[i]));
            }
#pragma unroll 1
            for (int i = (ntiles & 1) ? 1 : 0; i < ntiles; i += 2) {
                if (i > 0) g_tile(accA, accB, epi_type(i - 1), epi_dst(i - 1), epi_stride(i - 1), c, epi_pub(i - 1));
                g_tile(accB, accA, epi_type(i), epi_dst(i), epi_stride(i), c, epi_pub(i));
            }
            wgmma_wait<0>();
            fence_regs(accB);
            mbar_arrive_remote_if(rbars + (B_EMPTYG + ((c.sg - 1) & 3)) * 8, el);
            mbar_arrive_remote_if(rbars + B_XNFREE * 8, el);
#pragma unroll
            for (int j = 0; j < 16; j++) {
                qf[2 * j] = pack_bf16(accB[4 * j] * (rs0 * QSCALE), accB[4 * j + 1] * (rs0 * QSCALE));
                qf[2 * j + 1] = pack_bf16(accB[4 * j + 2] * (rs1 * QSCALE), accB[4 * j + 3] * (rs1 * QSCALE));
            }
        }
        TSTAMP(2);
        CSTAMP(15);

        {
            float sacc[64], oacc[64];
            uint32_t pf[32];
            float m0 = 0.f, m1 = 0.f, l0 = 0.f, l1 = 0.f, sc0 = 1.f, sc1 = 1.f, pl0 = 0.f, pl1 = 0.f;
            bool gen = false;
            auto rel = [&](uint32_t idx) { mbar_arrive_remote_if(rbars + idx * 8, el); };
#define WAITA2(a, b, c, d) mbar_wait2(a, b, c, d)
            int sa = 0;
            uint32_t pa = 0;
            auto adv = [&]() { const bool w = sa == NP - 1; sa = w ? 0 : sa + 1; pa ^= w ? 1u : 0u; };

            auto issue_qk = [&](uint32_t a0, uint32_t a1) {
                wgmma_fence();
#pragma unroll
                for (int kk = 0; kk < 4; kk++)
                    wgmma_rs_n128_kb(sacc, qf[4 * kk], qf[4 * kk + 1], qf[4 * kk + 2], qf[4 * kk + 3], a0 + kk * 2, kk != 0);
#pragma unroll
                for (int kk = 4; kk < 8; kk++)
                    wgmma_rs_n128_kb(sacc, qf[4 * kk], qf[4 * kk + 1], qf[4 * kk + 2], qf[4 * kk + 3], a1 + (kk - 4) * 2, 1);
                wgmma_commit();
            };
            auto issue_pv = [&](uint32_t a0, uint32_t a1, int acc_flag) {
                a0 = desc_lo(a0, 8192); a1 = desc_lo(a1, 8192);
                wgmma_fence();
#pragma unroll
                for (int kk = 0; kk < 4; kk++)
                    wgmma_rs_n128_tb(oacc, pf[4 * kk], pf[4 * kk + 1], pf[4 * kk + 2], pf[4 * kk + 3], a0 + kk * 128, kk != 0 ? 1 : acc_flag);
#pragma unroll
                for (int kk = 4; kk < 8; kk++)
                    wgmma_rs_n128_tb(oacc, pf[4 * kk], pf[4 * kk + 1], pf[4 * kk + 2], pf[4 * kk + 3], a1 + (kk - 4) * 128, 1);
                wgmma_commit();
            };
            auto rowmax = [&](float& x0, float& x1) {
                float a[4], b[4];
#pragma unroll
                for (int u = 0; u < 4; u++) {
                    a[u] = fmaxf(sacc[4 * u], sacc[4 * u + 1]);
                    b[u] = fmaxf(sacc[4 * u + 2], sacc[4 * u + 3]);
                }
#pragma unroll
                for (int j = 4; j < 16; j++) {
                    a[j & 3] = fmaxf(a[j & 3], fmaxf(sacc[4 * j], sacc[4 * j + 1]));
                    b[j & 3] = fmaxf(b[j & 3], fmaxf(sacc[4 * j + 2], sacc[4 * j + 3]));
                }
                x0 = fmaxf(fmaxf(a[0], a[1]), fmaxf(a[2], a[3]));
                x1 = fmaxf(fmaxf(b[0], b[1]), fmaxf(b[2], b[3]));
                x0 = fmaxf(x0, __shfl_xor_sync(0xffffffffu, x0, 1));
                x1 = fmaxf(x1, __shfl_xor_sync(0xffffffffu, x1, 1));
                x0 = fmaxf(x0, __shfl_xor_sync(0xffffffffu, x0, 2));
                x1 = fmaxf(x1, __shfl_xor_sync(0xffffffffu, x1, 2));
            };
            auto out_of_range = [&](bool first) {
                int a = __vimax3_s32(__float_as_int(sacc[0]), __float_as_int(sacc[1]), __float_as_int(sacc[2]));
                int b = __vimax3_s32(__float_as_int(sacc[3]), __float_as_int(sacc[4]), __float_as_int(sacc[5]));
                int c2 = __vimax3_s32(__float_as_int(sacc[6]), __float_as_int(sacc[7]), __float_as_int(sacc[8]));
                int d2 = __vimax3_s32(__float_as_int(sacc[9]), __float_as_int(sacc[10]), __float_as_int(sacc[11]));
#pragma unroll
                for (int i = 12; i < 60; i += 8) {
                    a = __vimax3_s32(a, __float_as_int(sacc[i]), __float_as_int(sacc[i + 1]));
                    b = __vimax3_s32(b, __float_as_int(sacc[i + 2]), __float_as_int(sacc[i + 3]));
                    c2 = __vimax3_s32(c2, __float_as_int(sacc[i + 4]), __float_as_int(sacc[i + 5]));
                    d2 = __vimax3_s32(d2, __float_as_int(sacc[i + 6]), __float_as_int(sacc[i + 7]));
                }
                a = __vimax3_s32(a, __float_as_int(sacc[60]), __float_as_int(sacc[61]));
                b = __vimax3_s32(b, __float_as_int(sacc[62]), __float_as_int(sacc[63]));
                bool bad = __vimax3_s32(a, b, max(c2, d2)) > 0x42800000;
                if (first) {
                    unsigned u0 = min(__float_as_uint(sacc[0]), __float_as_uint(sacc[1]));
                    unsigned u1 = min(__float_as_uint(sacc[2]), __float_as_uint(sacc[3]));
#pragma unroll
                    for (int j = 1; j < 16; j++) {
                        u0 = __vimin3_u32(u0, __float_as_uint(sacc[4 * j]), __float_as_uint(sacc[4 * j + 1]));
                        u1 = __vimin3_u32(u1, __float_as_uint(sacc[4 * j + 2]), __float_as_uint(sacc[4 * j + 3]));
                    }
                    bad = bad || max(u0, u1) > 0xC2800000u;
                }
                return __any_sync(0xffffffffu, bad) != 0;
            };
            auto exp_part = [&](auto J0_, auto J1_, float& t0, float& t1, float& u0, float& u1) {
#pragma unroll
                for (int j = decltype(J0_)::value; j < decltype(J1_)::value; j++) {
                    sacc[4 * j] = ex2(sacc[4 * j]); sacc[4 * j + 1] = ex2(sacc[4 * j + 1]);
                    sacc[4 * j + 2] = ex2(sacc[4 * j + 2]); sacc[4 * j + 3] = ex2(sacc[4 * j + 3]);
                    t0 += sacc[4 * j]; u0 += sacc[4 * j + 1];
                    t1 += sacc[4 * j + 2]; u1 += sacc[4 * j + 3];
                }
            };
            auto o_epilogue = [&](int hi, float a, float b) {
                store_tile128(g_oq + (size_t)row0 * (NH * DH) + (4 * g + hi) * 128 + 8 * q4, (size_t)8 * NH * DH, oacc, a, b);
                mbar_arrive_warp(bars + (B_PUB + 1 + hi) * 8, lane == 0);
            };
            constexpr int SPLIT = 12;
            if (wg == 1) named_arrive(1, 288);
#define PP_SYNC() named_sync(1 + wg, 288)
#define PP_ARRIVE() named_arrive(2 - wg, 288)
            const int sg0 = 10 * ntiles;
            uint32_t ka = desc_lo(sbase + OFF_RINGG + (sg0 & 3) * SLOT, 16);
            uint32_t kr = B_EMPTYA + NP;
#pragma unroll
            for (int i = 0; i < 64; i++) { asm volatile("" : "=f"(oacc[i])); asm volatile("" : "=f"(sacc[i])); }
#pragma unroll
            for (int i = 0; i < 32; i++) asm volatile("" : "=r"(pf[i]));
#pragma unroll 1
            for (int it = 0; it < 16; it++) {
                const int j = it & 3;
                ISTAMP(it);
                FWRAP(0, PP_SYNC());
                FWRAP(7, issue_qk(ka, ka + (SLOT >> 4)));
                const uint32_t kc = kr;
                const int va = sa;
                if (it > 0) adv();
                if (it == 0) {
                    ka = desc_lo(sbase + OFF_RINGG + ((sg0 + 2) & 3) * SLOT, 16); kr = B_EMPTYA + NP + 1;
                } else if (it < 15) {
                    ka = desc_lo(sbase + sa * 2 * SLOT, 16); kr = B_EMPTYA + sa;
                    adv();
                }
                if (j == 1 && it > 1) o_epilogue((it >> 2) - 1, pl0, pl1);
                const __nv_bfloat16* qsrc = g_oq + (size_t)row0 * (NH * DH) + (4 * g + (it >> 2) + 1) * 128 + 8 * q4;
                if (j == 2 && it < 14) {
                    asm volatile("prefetch.global.L1 [%0];" :: "l"(qsrc));
                    asm volatile("prefetch.global.L1 [%0];" :: "l"(qsrc + 64));
                    asm volatile("prefetch.global.L1 [%0];" :: "l"(qsrc + (size_t)8 * NH * DH));
                    asm volatile("prefetch.global.L1 [%0];" :: "l"(qsrc + (size_t)8 * NH * DH + 64));
                }
                if (it > 0) FWRAP(2, issue_pv(sbase + va * 2 * SLOT, sbase + (va * 2 + 1) * SLOT, j != 1));
                else wgmma_commit();
                PP_ARRIVE();
                FWRAP(3, wgmma_wait<1>());
                fence_regs(sacc);
                float t0 = 0.f, t1 = 0.f, u0 = 0.f, u1 = 0.f;
                {
                    rel(kc);
                    if (j == 3 && it < 15) {
#pragma unroll
                        for (int m = 0; m < 4; m++) {
                            uint4 u0 = *reinterpret_cast<const uint4*>(qsrc + 32 * m);
                            uint4 u1 = *reinterpret_cast<const uint4*>(qsrc + (size_t)8 * NH * DH + 32 * m);
                            qf[8 * m + 0] = u0.x; qf[8 * m + 1] = u0.y; qf[8 * m + 2] = u0.z; qf[8 * m + 3] = u0.w;
                            qf[8 * m + 4] = u1.x; qf[8 * m + 5] = u1.y; qf[8 * m + 6] = u1.z; qf[8 * m + 7] = u1.w;
                        }
                    }
                    if (j == 0) { l0 = 0.f; l1 = 0.f; m0 = 0.f; m1 = 0.f; gen = false; }
                    if (!gen) gen = out_of_range(j == 0);
                    if (gen) {
                        float x0, x1;
                        rowmax(x0, x1);
                        if (j != 0) {
                            x0 = fmaxf(x0, m0); x1 = fmaxf(x1, m1);
                            sc0 = ex2(m0 - x0); sc1 = ex2(m1 - x1);
                            l0 *= sc0; l1 *= sc1;
                        }
                        m0 = x0; m1 = x1;
#pragma unroll
                        for (int jj = 0; jj < 16; jj++) {
                            sacc[4 * jj] -= m0; sacc[4 * jj + 1] -= m0;
                            sacc[4 * jj + 2] -= m1; sacc[4 * jj + 3] -= m1;
                        }
                    }
                    exp_part(IC<0>{}, IC<SPLIT>{}, t0, t1, u0, u1);
                }
                asm volatile("st.shared.f32 [%0], %1;" :: "r"(bars + 512), "f"((t0 + u0) + (t1 + u1)) : "memory");
                FWRAP(5, wgmma_wait<0>());
                fence_regs(oacc);
                fence_regs(pf);
                if (it > 0) rel(B_EMPTYA + va);
                {
                    exp_part(IC<SPLIT>{}, IC<16>{}, t0, t1, u0, u1);
                    l0 += t0 + u0; l1 += t1 + u1;
#pragma unroll
                    for (int jj = 0; jj < 16; jj++) {
                        pf[2 * jj] = pack_bf16(sacc[4 * jj], sacc[4 * jj + 1]);
                        pf[2 * jj + 1] = pack_bf16(sacc[4 * jj + 2], sacc[4 * jj + 3]);
                    }
                    if (j != 0 && gen) {
#pragma unroll
                        for (int jj = 0; jj < 16; jj++) {
                            oacc[4 * jj] *= sc0; oacc[4 * jj + 1] *= sc0;
                            oacc[4 * jj + 2] *= sc1; oacc[4 * jj + 3] *= sc1;
                        }
                    }
                    if (j == 3) {
                        float a = l0, b = l1;
                        a += __shfl_xor_sync(0xffffffffu, a, 1); b += __shfl_xor_sync(0xffffffffu, b, 1);
                        a += __shfl_xor_sync(0xffffffffu, a, 2); b += __shfl_xor_sync(0xffffffffu, b, 2);
                        pl0 = rcp(a); pl1 = rcp(b);
                    }
                }
            }
            {
                ISTAMP(16);
                PP_SYNC();
                issue_pv(sbase + (NP - 1) * 2 * SLOT, sbase + ((NP - 1) * 2 + 1) * SLOT, 1);
                if (wg == 0) named_arrive(2, 288);
                wgmma_wait<0>();
                fence_regs(oacc);
                rel(B_EMPTYA + NP - 1);
            }
            ISTAMP(17);
            o_epilogue(3, pl0, pl1);
            ISTAMP(18);
            CSTAMP(13);
        }
        TSTAMP(3);

        {
            float a192[96], a128[64];
#pragma unroll 1
            for (int i = 0; i < nblk; i++) {
                const int st = i & 3;
                mbar_wait_u(bars + (B_FULL3 + st) * 8, (i >> 2) & 1);
                const uint32_t base = sbase + ((st + 3) & 3) * ST3;
                const uint32_t da = desc_lo(base + wg * 8192, 16);
                const uint32_t db = desc_lo(base + SLOT, 4096);
                wgmma_fence();
#pragma unroll
                for (int kk = 0; kk < 4; kk++) {
                    const uint32_t bb = db + (kk >> 1) * (20480 >> 4) + (kk & 1) * (2048 >> 4);
                    wgmma_ss_n192_tb(a192, da + kk * 2, bb, (i | kk) != 0);
                    wgmma_ss_n128_tb(a128, da + kk * 2, bb + ((3 * 4096) >> 4), (i | kk) != 0);
                }
                wgmma_commit();
                if (i > 0) {
                    wgmma_wait<1>();
                    mbar_arrive_remote_if(rbars + (B_EMPTY3 + ((i - 1) & 3)) * 8, el);
                }
            }
            wgmma_wait<0>();
            fence_regs(a192);
            fence_regs(a128);
            mbar_arrive_remote_if(rbars + (B_EMPTY3 + ((nblk - 1) & 3)) * 8, el);
            TSTAMP(4);
            CSTAMP(0);
            TSTAMP_T(30, 128);

            const int kq = g >> 1;
            named_sync(5, 256);
            CSTAMP(1);
            uint4* const part = g_part + (size_t)((t * 2 + (g & 1)) * 4 + kq) * 4 * (PSLAB / 16) + tid;
            static_for<0, 4>([&](auto S_) {
                constexpr int sl = decltype(S_)::value;
                uint4 w[5];
                static_for<0, 5>([&](auto I_) {
                    constexpr int i = decltype(I_)::value;
                    constexpr int jn = sl * 10 + 2 * i;
                    auto pk = [&](auto J_, int h) {
                        constexpr int j = decltype(J_)::value;
                        if constexpr (j < 24) return pack_bf16(a192[4 * j + h], a192[4 * j + h + 1]);
                        else return pack_bf16(a128[4 * (j - 24) + h], a128[4 * (j - 24) + h + 1]);
                    };
                    w[i] = make_uint4(pk(IC<jn>{}, 0), pk(IC<jn>{}, 2), pk(IC<jn + 1>{}, 0), pk(IC<jn + 1>{}, 2));
                });
                if (sl == kq) {
#pragma unroll
                    for (int i = 0; i < 5; i++)
                        asm volatile("st.shared.v4.b32 [%0], {%1, %2, %3, %4};"
                                     :: "r"(sbase + kq * PSLAB + (i * 256 + tid) * 16), "r"(w[i].x), "r"(w[i].y), "r"(w[i].z), "r"(w[i].w) : "memory");
                } else {
#pragma unroll
                    for (int i = 0; i < 5; i++) __stcg(part + sl * (PSLAB / 16) + i * 256, w[i]);
                }
            });
            CSTAMP(2);
            CSTAMP(3);
            mbar_arrive_warp(bars + (B_PUB + 5) * 8, lane == 0);
            CSTAMP(4);
            TSTAMP(5);
            auto src_addr = [&](int src) { return sbase + (src == kq ? kq : 4 + (src < kq ? src : src - 1)) * PSLAB + tid * 16; };
            auto src_bar = [&](int src) { return bars + (B_IN + (src < kq ? src : src - 1)) * 8; };
            if (kq != 3) mbar_wait_u(src_bar(3), 0);
            TSTAMP(25);
            CSTAMP(5);
            {
                const uint32_t ga = src_addr(3);
#pragma unroll 1
                for (int i = 0; i < 5; i++) {
                    uint32_t w[4];
                    asm volatile("ld.shared.v4.b32 {%0, %1, %2, %3}, [%4];" : "=r"(w[0]), "=r"(w[1]), "=r"(w[2]), "=r"(w[3]) : "r"(ga + i * 4096) : "memory");
#pragma unroll
                    for (int e = 0; e < 4; e++) {
                        const float r2 = (e & 1) ? rs1 * rs1 : rs0 * rs0;
                        const uint32_t gb = pack_bf16(bf_lo(w[e]) * r2, bf_hi(w[e]) * r2);
                        w[e] = pack_bf16(silu_f(bf_lo(gb)), silu_f(bf_hi(gb)));
                    }
                    asm volatile("st.shared.v4.b32 [%0], {%1, %2, %3, %4};" :: "r"(ga + i * 4096), "r"(w[0]), "r"(w[1]), "r"(w[2]), "r"(w[3]) : "memory");
                }
            }
            mbar_wait_u(bars + B_XS * 8, 0);
#pragma unroll 1
            for (int v = 0; v < 3; v++) if (v != kq) mbar_wait_u(src_bar(v), 0);
            TSTAMP(27);
            CSTAMP(6); CSTAMP(7);
            {
                const uint32_t s0a = src_addr(0), s1a = src_addr(1), s2a = src_addr(2), ga = src_addr(3);
                const uint32_t xs = sbase + XS_OFF + (wg * 64 + wl * 16 + (lane >> 2)) * 160 + q4 * 4;
                uint32_t p0[20], p1[20], p2[20], a[20], x[20];
#pragma unroll
                for (int i = 0; i < 5; i++) {
                    asm volatile("ld.shared.v4.b32 {%0, %1, %2, %3}, [%4];" : "=r"(p0[4 * i]), "=r"(p0[4 * i + 1]), "=r"(p0[4 * i + 2]), "=r"(p0[4 * i + 3]) : "r"(s0a + i * 4096) : "memory");
                    asm volatile("ld.shared.v4.b32 {%0, %1, %2, %3}, [%4];" : "=r"(p1[4 * i]), "=r"(p1[4 * i + 1]), "=r"(p1[4 * i + 2]), "=r"(p1[4 * i + 3]) : "r"(s1a + i * 4096) : "memory");
                    asm volatile("ld.shared.v4.b32 {%0, %1, %2, %3}, [%4];" : "=r"(p2[4 * i]), "=r"(p2[4 * i + 1]), "=r"(p2[4 * i + 2]), "=r"(p2[4 * i + 3]) : "r"(s2a + i * 4096) : "memory");
                    asm volatile("ld.shared.v4.b32 {%0, %1, %2, %3}, [%4];" : "=r"(a[4 * i]), "=r"(a[4 * i + 1]), "=r"(a[4 * i + 2]), "=r"(a[4 * i + 3]) : "r"(ga + i * 4096) : "memory");
#pragma unroll
                    for (int e = 0; e < 4; e++)
                        asm volatile("ld.shared.b32 %0, [%1];" : "=r"(x[4 * i + e]) : "r"(xs + (e & 1) * 8 * 160 + (2 * i + (e >> 1)) * 16) : "memory");
                }
#pragma unroll
                for (int i = 0; i < 20; i++) {
                    const uint32_t sb = pack_bf16(bf_lo(p0[i]) + bf_lo(p1[i]) + bf_lo(p2[i]), bf_hi(p0[i]) + bf_hi(p1[i]) + bf_hi(p2[i]));
                    const uint32_t r = hmul2_bf16(sb, a[i]);
                    const uint32_t o = pack_bf16(bf_lo(x[i]) + bf_lo(r), bf_hi(x[i]) + bf_hi(r));
                    asm volatile("st.shared.b32 [%0], %1;" :: "r"(xs + (i & 1) * 8 * 160 + (2 * (i >> 2) + ((i >> 1) & 1)) * 16), "r"(o) : "memory");
                }
            }
            TSTAMP(28);
            CSTAMP(8);
            asm volatile("fence.proxy.async.shared::cta;" ::: "memory");
            named_sync(5, 256);
            TSTAMP(29);
            CSTAMP(9);
            if (tid == 0) {
                asm volatile("cp.async.bulk.tensor.2d.global.shared::cta.bulk_group [%0, {%2, %3}], [%1];"
                             :: "l"(&tm_out), "r"(sbase + XS_OFF), "r"((g & 1) * 320 + kq * 80), "r"(t * 128) : "memory");
                asm volatile("cp.async.bulk.commit_group;" ::: "memory");
                asm volatile("cp.async.bulk.wait_group.read 0;" ::: "memory");
            }
            TSTAMP(6);
            CSTAMP(10);
        }
    }
}

typedef CUresult (*PFN_encodeTiled)(CUtensorMap*, CUtensorMapDataType, cuuint32_t, void*, const cuuint64_t*, const cuuint64_t*,
                                    const cuuint32_t*, const cuuint32_t*, CUtensorMapInterleave, CUtensorMapSwizzle,
                                    CUtensorMapL2promotion, CUtensorMapFloatOOBfill);

bool encode(PFN_encodeTiled fn, CUtensorMap* m, const void* base, int rank, const cuuint64_t* dims, const cuuint64_t* strides,
            const cuuint32_t* box) {
    cuuint32_t es[5] = {1, 1, 1, 1, 1};
    return fn(m, CU_TENSOR_MAP_DATA_TYPE_BFLOAT16, rank, const_cast<void*>(base), dims, strides, box, es,
              CU_TENSOR_MAP_INTERLEAVE_NONE, CU_TENSOR_MAP_SWIZZLE_128B, CU_TENSOR_MAP_L2_PROMOTION_L2_128B,
              CU_TENSOR_MAP_FLOAT_OOB_FILL_NONE) == CUDA_SUCCESS;
}
bool encode2d(PFN_encodeTiled fn, CUtensorMap* m, const void* base, uint64_t cols, uint64_t rows, uint32_t box_rows) {
    cuuint64_t dims[2] = {cols, rows};
    cuuint64_t strides[1] = {cols * 2};
    cuuint32_t box[2] = {64, box_rows};
    return encode(fn, m, base, 2, dims, strides, box);
}
bool encode_out(PFN_encodeTiled fn, CUtensorMap* m, void* base) {
    cuuint64_t dims[2] = {DM, S_LEN};
    cuuint64_t strides[1] = {DM * 2};
    cuuint32_t box[2] = {80, 128};
    cuuint32_t es[2] = {1, 1};
    return fn(m, CU_TENSOR_MAP_DATA_TYPE_BFLOAT16, 2, base, dims, strides, box, es, CU_TENSOR_MAP_INTERLEAVE_NONE,
              CU_TENSOR_MAP_SWIZZLE_NONE, CU_TENSOR_MAP_L2_PROMOTION_NONE, CU_TENSOR_MAP_FLOAT_OOB_FILL_NONE) == CUDA_SUCCESS;
}
bool encode_perm(PFN_encodeTiled fn, CUtensorMap* m, const void* base, uint64_t rows) {
    cuuint64_t dims[5] = {64, 2, rows / 8, 4, 10};
    cuuint64_t strides[4] = {DM * 2, 8 * DM * 2, 2 * DM * 2, 128};
    cuuint32_t box[5] = {64, 2, 4, 4, 5};
    return encode(fn, m, base, 5, dims, strides, box);
}

}

extern "C" void kernel_launch(void* const* d_in, const int* in_sizes, int n_in, void* d_out, int out_size) {
    (void)in_sizes; (void)n_in; (void)out_size;
    static PFN_encodeTiled enc = nullptr;
    static void* p_oq = nullptr;
    static void* p_h = nullptr;
    if (!enc) {
        void* p = nullptr;
        cudaDriverEntryPointQueryResult qr;
        if (cudaGetDriverEntryPoint("cuTensorMapEncodeTiled", &p, cudaEnableDefault, &qr) != cudaSuccess || !p) {
            fprintf(stderr, "cuTensorMapEncodeTiled not found\n");
            return;
        }
        enc = (PFN_encodeTiled)p;
        cudaGetSymbolAddress(&p_oq, g_oq);
        cudaGetSymbolAddress(&p_h, g_h);
        cudaFuncSetAttribute(fused_kernel, cudaFuncAttributeMaxDynamicSharedMemorySize, SMEM_BYTES);
    }
    const void* x = d_in[0];
    const void* kc = d_in[1];
    const void* vc = d_in[2];
    const void* wq = d_in[3];
    const void* wo = d_in[4];
    const void* w1 = d_in[6];
    const void* w3 = d_in[7];
    const void* w2 = d_in[8];
    CUtensorMap tm_w1, tm_w3, tm_wq, tm_k, tm_v, tm_wo, tm_w2, tm_o, tm_h, tm_x, tm_out, tm_xs;
    bool ok = encode2d(enc, &tm_w1, w1, FF, DM, 64) && encode2d(enc, &tm_w3, w3, FF, DM, 64) &&
              encode2d(enc, &tm_wq, wq, NH * DH, DM, 64) && encode2d(enc, &tm_k, kc, DH, (uint64_t)NH * SKV, 64) &&
              encode2d(enc, &tm_v, vc, DH, (uint64_t)NH * SKV, 64) && encode_perm(enc, &tm_wo, wo, NH * DH) &&
              encode_perm(enc, &tm_w2, w2, FF) && encode2d(enc, &tm_o, p_oq, NH * DH, S_LEN, 128) &&
              encode2d(enc, &tm_h, p_h, FF, S_LEN, 128) && encode2d(enc, &tm_x, x, DM, S_LEN, 128) && encode_out(enc, &tm_out, d_out) && encode_out(enc, &tm_xs, const_cast<void*>(x));
    if (!ok) { fprintf(stderr, "tensor map encode failed\n"); return; }
    Params prm;
    prm.x = (const __nv_bfloat16*)x;
    prm.out = (__nv_bfloat16*)d_out;
    cudaLaunchConfig_t cfg = {};
    cfg.gridDim = dim3(128);
    cfg.blockDim = dim3(384);
    cfg.dynamicSmemBytes = SMEM_BYTES;
    cfg.stream = cudaStreamPerThread;
    cudaLaunchAttribute at[1];
    at[0].id = cudaLaunchAttributeClusterDimension;
    at[0].val.clusterDim.x = 2; at[0].val.clusterDim.y = 1; at[0].val.clusterDim.z = 1;
    cfg.attrs = at;
    cfg.numAttrs = 1;
    cudaError_t e = cudaLaunchKernelEx(&cfg, fused_kernel, tm_w1, tm_w3, tm_wq, tm_k, tm_v, tm_wo, tm_w2, tm_o, tm_h, tm_x, tm_out, tm_xs, prm);
    if (e != cudaSuccess) fprintf(stderr, "launch failed: %s\n", cudaGetErrorString(e));
}
```

```cpp
#include <cuda_runtime.h>
#include <cuda_bf16.h>
#include <cuda.h>
#include <stdint.h>
#include <stdio.h>

namespace {

constexpr int S_LEN = 2048, DM = 640, NH = 32, DH = 128, SKV = 2048, WIN = 512, KOFF = SKV - WIN, FF = 1728;
constexpr int SLOT = 16384;
constexpr int OFF_RINGG = 10 * SLOT;
constexpr int OFF_BAR = 14 * SLOT;
constexpr int SMEM_BYTES = OFF_BAR + 1024 + 1024;
constexpr int ST3 = 57344;

constexpr int NP = 5;
enum { B_FULLG = 0, B_EMPTYG = 4, B_FULLA = 8, B_EMPTYA = 15, B_FULL3 = 22, B_EMPTY3 = 26, B_XNFREE = 30, B_PUB = 31, B_IN = 39, B_X = 42, B_XS = 52, B_FREE = 53, B_COUNT = 54 };

__device__ __align__(1024) __nv_bfloat16 g_oq[S_LEN * NH * DH];
__device__ __align__(1024) __nv_bfloat16 g_h[S_LEN * FF];
__device__ __align__(1024) uint4 g_part[32 * 4 * 4 * 5 * 256];
__device__ __align__(1024) unsigned g_cnt[16 * 128];

constexpr uint32_t PK_UNITS[2] = {0x22344444u, 0x22334444u};
constexpr uint64_t PK_USTART[2] = {0x191714100c080400ull, 0x181613100c080400ull};
constexpr uint64_t PK_NBLK[2] = {0x1b1b181614151415ull, 0x1b1b181814141414ull};
__constant__ uint8_t c_blk[2][8][28] = {
    {
     { 0,  1,  8,  9, 16,  2,  3, 10, 11, 18,  4,  5, 12, 13, 20,  6,  7, 14, 15, 22, 23,  0,  0,  0,  0,  0,  0,  0},
     { 0,  1,  8,  9, 16,  2,  3, 10, 11, 18,  4,  5, 12, 13, 20,  6,  7, 14, 15, 22,  0,  0,  0,  0,  0,  0,  0,  0},
     {17, 24, 25, 32, 33, 19, 26, 27, 34, 35, 21, 28, 29, 36, 37, 44, 30, 31, 38, 39, 46,  0,  0,  0,  0,  0,  0,  0},
     {17, 24, 25, 32, 33, 19, 26, 27, 34, 35, 21, 28, 29, 36, 37, 23, 30, 31, 38, 39,  0,  0,  0,  0,  0,  0,  0,  0},
     {40, 41, 48, 49, 56, 57, 42, 43, 50, 51, 58, 59, 45, 52, 53, 60, 61, 47, 54, 55, 62, 63,  0,  0,  0,  0,  0,  0},
     {40, 41, 48, 49, 56, 57, 42, 43, 50, 51, 58, 59, 44, 45, 52, 53, 60, 61, 46, 47, 54, 55, 62, 63,  0,  0,  0,  0},
     { 0,  1,  2,  3,  4,  5,  6,  7,  8,  9, 10, 11, 12, 13, 14, 15, 16, 17, 18, 19, 20, 21, 22, 23, 24, 25, 26,  0},
     { 0,  1,  2,  3,  4,  5,  6,  7,  8,  9, 10, 11, 12, 13, 14, 15, 16, 17, 18, 19, 20, 21, 22, 23, 24, 25, 26,  0},
    },
    {
     { 0,  1,  8,  9, 16,  2,  3, 10, 11, 18,  4,  5, 12, 13, 20,  6,  7, 14, 15, 22,  0,  0,  0,  0,  0,  0,  0,  0},
     { 0,  1,  8,  9, 16,  2,  3, 10, 11, 18,  4,  5, 12, 13, 20,  6,  7, 14, 15, 22,  0,  0,  0,  0,  0,  0,  0,  0},
     {17, 24, 25, 32, 33, 19, 26, 27, 34, 35, 21, 28, 29, 36, 37, 23, 30, 31, 38, 39,  0,  0,  0,  0,  0,  0,  0,  0},
     {17, 24, 25, 32, 33, 19, 26, 27, 34, 35, 21, 28, 29, 36, 37, 23, 30, 31, 38, 39,  0,  0,  0,  0,  0,  0,  0,  0},
     {40, 41, 48, 49, 56, 57, 42, 43, 50, 51, 58, 59, 44, 45, 52, 53, 60, 61, 46, 47, 54, 55, 62, 63,  0,  0,  0,  0},
     {40, 41, 48, 49, 56, 57, 42, 43, 50, 51, 58, 59, 44, 45, 52, 53, 60, 61, 46, 47, 54, 55, 62, 63,  0,  0,  0,  0},
     { 0,  1,  2,  3,  4,  5,  6,  7,  8,  9, 10, 11, 12, 13, 14, 15, 16, 17, 18, 19, 20, 21, 22, 23, 24, 25, 26,  0},
     { 0,  1,  2,  3,  4,  5,  6,  7,  8,  9, 10, 11, 12, 13, 14, 15, 16, 17, 18, 19, 20, 21, 22, 23, 24, 25, 26,  0},
    },
};

__device__ __forceinline__ uint32_t smem_u32(const void* p) { return (uint32_t)__cvta_generic_to_shared(p); }
__device__ __forceinline__ void mbar_init(uint32_t bar, uint32_t count) {
    asm volatile("mbarrier.init.shared::cta.b64 [%0], %1;" :: "r"(bar), "r"(count));
}
__device__ __forceinline__ void mbar_expect_tx(uint32_t bar, uint32_t bytes) {
    asm volatile("mbarrier.arrive.expect_tx.shared::cta.b64 _, [%0], %1;" :: "r"(bar), "r"(bytes) : "memory");
}
__device__ __forceinline__ void mbar_arrive(uint32_t bar) {
    asm volatile("mbarrier.arrive.shared::cta.b64 _, [%0];" :: "r"(bar) : "memory");
}
__device__ __forceinline__ void mbar_wait(uint32_t bar, uint32_t parity, int code = 0) {
    (void)code;
    asm volatile("{\n.reg .pred p, q;\n.reg .u64 t0, t1;\n"
                 "mbarrier.try_wait.parity.shared::cta.b64 p, [%0], %1;\n"
                 "@p bra DONE;\n"
                 "mov.u64 t0, %%clock64;\n"
                 "LOOP:\n"
                 "mbarrier.try_wait.parity.shared::cta.b64 p, [%0], %1;\n"
                 "@p bra DONE;\n"
                 "mov.u64 t1, %%clock64;\n"
                 "sub.u64 t1, t1, t0;\n"
                 "setp.lt.u64 q, t1, 4000000000;\n"
                 "@q bra LOOP;\n"
                 "trap;\n"
                 "DONE:\n}"
                 :: "r"(bar), "r"(parity) : "memory");
}
__device__ __forceinline__ void mbar_wait_u(uint32_t bar, uint32_t parity) {
    asm volatile("{\n.reg .pred p, q;\n.reg .u64 t0, t1;\n"
                 "mbarrier.try_wait.parity.shared::cta.b64 p, [%0], %1;\n"
                 "vote.sync.all.pred p, p, 0xffffffff;\n"
                 "@p bra.uni DONE;\n"
                 "mov.u64 t0, %%clock64;\n"
                 "LOOP:\n"
                 "mbarrier.try_wait.parity.shared::cta.b64 p, [%0], %1;\n"
                 "vote.sync.all.pred p, p, 0xffffffff;\n"
                 "@p bra.uni DONE;\n"
                 "mov.u64 t1, %%clock64;\n"
                 "sub.u64 t1, t1, t0;\n"
                 "setp.lt.u64 q, t1, 4000000000;\n"
                 "vote.sync.any.pred q, q, 0xffffffff;\n"
                 "@q bra.uni LOOP;\n"
                 "trap;\n"
                 "DONE:\n}"
                 :: "r"(bar), "r"(parity) : "memory");
}
__device__ __forceinline__ uint32_t mbar_probe(uint32_t b0, uint32_t p0) {
    uint32_t ok;
    asm volatile("{\n.reg .pred p;\nmbarrier.test_wait.parity.shared::cta.b64 p, [%1], %2;\nselp.u32 %0, 1, 0, p;\n}"
                 : "=r"(ok) : "r"(b0), "r"(p0) : "memory");
    return ok;
}
__device__ __forceinline__ uint32_t mapa_u32(uint32_t addr, uint32_t cta) {
    uint32_t r;
    asm("mapa.shared::cluster.u32 %0, %1, %2;" : "=r"(r) : "r"(addr), "r"(cta));
    return r;
}
__device__ __forceinline__ void mbar_arrive_remote_if(uint32_t cluster_addr, uint32_t flag) {
    asm volatile("{\n.reg .pred p;\nsetp.ne.u32 p, %1, 0;\n@p mbarrier.arrive.shared::cluster.b64 _, [%0];\n}"
                 :: "r"(cluster_addr), "r"(flag) : "memory");
}
__device__ __forceinline__ void mbar_arrive_warp(uint32_t addr, uint32_t lane_flag) {
    __syncwarp();
    asm volatile("{\n.reg .pred p;\nsetp.ne.u32 p, %1, 0;\n@p mbarrier.arrive.shared::cta.b64 _, [%0];\n}"
                 :: "r"(addr), "r"(lane_flag) : "memory");
}
__device__ __forceinline__ void tma_2d_mc(uint32_t dst, const CUtensorMap* m, int c0, int c1, uint32_t bar) {
    asm volatile("cp.async.bulk.tensor.2d.shared::cluster.global.mbarrier::complete_tx::bytes.multicast::cluster"
                 " [%0], [%1, {%3, %4}], [%2], %5;"
                 :: "r"(dst), "l"(m), "r"(bar), "r"(c0), "r"(c1), "h"((uint16_t)3) : "memory");
}
__device__ __forceinline__ void tma_2d(uint32_t dst, const CUtensorMap* m, int c0, int c1, uint32_t bar) {
    asm volatile("cp.async.bulk.tensor.2d.shared::cluster.global.mbarrier::complete_tx::bytes [%0], [%1, {%3, %4}], [%2];"
                 :: "r"(dst), "l"(m), "r"(bar), "r"(c0), "r"(c1) : "memory");
}
__device__ __forceinline__ void tma_5d_mc(uint32_t dst, const CUtensorMap* m, int c2, int c4, uint32_t bar) {
    asm volatile("cp.async.bulk.tensor.5d.shared::cluster.global.mbarrier::complete_tx::bytes.multicast::cluster"
                 " [%0], [%1, {%5, %5, %3, %5, %4}], [%2], %6;"
                 :: "r"(dst), "l"(m), "r"(bar), "r"(c2), "r"(c4), "r"(0), "h"((uint16_t)3) : "memory");
}
__device__ __forceinline__ void bulk_load(uint32_t dst, const void* src, uint32_t bytes, uint32_t bar) {
    asm volatile("cp.async.bulk.shared::cluster.global.mbarrier::complete_tx::bytes [%0], [%1], %2, [%3];"
                 :: "r"(dst), "l"(src), "r"(bytes), "r"(bar) : "memory");
}
__device__ __forceinline__ void prefetch_2d(const CUtensorMap* m, int c0, int c1) {
    asm volatile("cp.async.bulk.prefetch.tensor.2d.L2.global [%0, {%1, %2}];" :: "l"(m), "r"(c0), "r"(c1) : "memory");
}
__device__ __forceinline__ void prefetch_5d(const CUtensorMap* m, int c2, int c4) {
    asm volatile("cp.async.bulk.prefetch.tensor.5d.L2.global [%0, {%3, %3, %1, %3, %2}];" :: "l"(m), "r"(c2), "r"(c4), "r"(0) : "memory");
}
__device__ __forceinline__ void prefetch_tmap(const CUtensorMap* m) { asm volatile("prefetch.tensormap [%0];" :: "l"(m) : "memory"); }
__device__ __forceinline__ void cluster_arrive_relaxed() { asm volatile("barrier.cluster.arrive.relaxed.aligned;" ::: "memory"); }
__device__ __forceinline__ void cluster_wait() { asm volatile("barrier.cluster.wait.acquire.aligned;" ::: "memory"); }
__device__ __forceinline__ void mma_bf16(float (&d)[4], uint32_t a0, uint32_t a1, uint32_t a2, uint32_t a3, uint32_t b0, uint32_t b1) {
    asm volatile("mma.sync.aligned.m16n8k16.row.col.f32.bf16.bf16.f32 {%0, %1, %2, %3}, {%4, %5, %6, %7}, {%8, %9}, {%0, %1, %2, %3};"
                 : "+f"(d[0]), "+f"(d[1]), "+f"(d[2]), "+f"(d[3]) : "r"(a0), "r"(a1), "r"(a2), "r"(a3), "r"(b0), "r"(b1));
}
__device__ __forceinline__ uint32_t hsub2_bf16(uint32_t a, uint32_t b) { uint32_t r; asm("sub.rn.bf16x2 %0, %1, %2;" : "=r"(r) : "r"(a), "r"(b)); return r; }
__device__ __forceinline__ uint32_t cluster_ctarank() { uint32_t r; asm volatile("mov.u32 %0, %%cluster_ctarank;" : "=r"(r)); return r; }
__device__ __forceinline__ void wgmma_fence() { asm volatile("wgmma.fence.sync.aligned;" ::: "memory"); }
__device__ __forceinline__ void wgmma_commit() { asm volatile("wgmma.commit_group.sync.aligned;" ::: "memory"); }
template <int N> __device__ __forceinline__ void wgmma_wait() { asm volatile("wgmma.wait_group.sync.aligned %0;" :: "n"(N) : "memory"); }
template <int N> __device__ __forceinline__ void fence_regs(float (&d)[N]) {
#pragma unroll
    for (int i = 0; i < N; i++) asm volatile("" : "+f"(d[i]) :: "memory");
}
template <int N> __device__ __forceinline__ void fence_regs(uint32_t (&d)[N]) {
#pragma unroll
    for (int i = 0; i < N; i++) asm volatile("" : "+r"(d[i]) :: "memory");
}
__device__ __forceinline__ void named_sync(int id, int n) { asm volatile("bar.sync %0, %1;" :: "r"(id), "r"(n) : "memory"); }
__device__ __forceinline__ void named_arrive(int id, int n) { asm volatile("bar.arrive %0, %1;" :: "r"(id), "r"(n) : "memory"); }
__device__ __forceinline__ uint32_t desc_lo(uint32_t addr, uint32_t lbo_bytes) {
    return ((addr & 0x3FFFF) >> 4) | ((lbo_bytes >> 4) << 16);
}
__device__ __forceinline__ uint32_t pack_bf16(float lo, float hi) {
    uint32_t r;
    asm("cvt.rn.bf16x2.f32 %0, %1, %2;" : "=r"(r) : "f"(hi), "f"(lo));
    return r;
}
__device__ __forceinline__ float bf_lo(uint32_t v) { return __uint_as_float(v << 16); }
__device__ __forceinline__ float bf_hi(uint32_t v) { return __uint_as_float(v & 0xffff0000u); }
__device__ __forceinline__ float bf_round(float x) { return bf_lo(pack_bf16(x, 0.f)); }
__device__ __forceinline__ float ex2(float x) { float r; asm("ex2.approx.ftz.f32 %0, %1;" : "=f"(r) : "f"(x)); return r; }
__device__ __forceinline__ float rcp(float x) { float r; asm("rcp.approx.ftz.f32 %0, %1;" : "=f"(r) : "f"(x)); return r; }
__device__ __forceinline__ float silu_f(float x) { return x * rcp(1.0f + ex2(x * -1.4426950408889634f)); }
__device__ __forceinline__ uint32_t hmul2_bf16(uint32_t a, uint32_t b) {
    uint32_t r;
    asm("mul.rn.bf16x2 %0, %1, %2;" : "=r"(r) : "r"(a), "r"(b));
    return r;
}
__device__ __forceinline__ unsigned ld_acquire(const unsigned* p) {
    unsigned v;
    asm volatile("ld.acquire.gpu.global.u32 %0, [%1];" : "=r"(v) : "l"(p) : "memory");
    return v;
}
__device__ __forceinline__ void red_release(unsigned* p, unsigned v) {
    asm volatile("red.release.gpu.global.add.u32 [%0], %1;" :: "l"(p), "r"(v) : "memory");
}
__device__ __forceinline__ void wait_flag(const unsigned* p, unsigned target, int code) {
    (void)code;
    if ((int)(ld_acquire(p) - target) >= 0) return;
    long long t0 = clock64();
    while ((int)(ld_acquire(p) - target) < 0) {
        __nanosleep(40);
        if (clock64() - t0 > 4000000000ll) __trap();
    }
}

__device__ __forceinline__ void wgmma_ss_n128_tb(float (&d)[64], uint32_t da, uint32_t db, int scale_d) {
    asm volatile("{\n.reg .pred p;\n.reg .b64 da, db;\nsetp.ne.b32 p, %66, 0;\n"
        "mov.b64 da, {%64, 0x40000040};\nmov.b64 db, {%65, 0x40000040};\n"
        "wgmma.mma_async.sync.aligned.m64n128k16.f32.bf16.bf16 "
        "{%0, %1, %2, %3, %4, %5, %6, %7, %8, %9, %10, %11, %12, %13, %14, %15, "
        "%16, %17, %18, %19, %20, %21, %22, %23, %24, %25, %26, %27, %28, %29, %30, %31, "
        "%32, %33, %34, %35, %36, %37, %38, %39, %40, %41, %42, %43, %44, %45, %46, %47, "
        "%48, %49, %50, %51, %52, %53, %54, %55, %56, %57, %58, %59, %60, %61, %62, %63}, "
        "da, db, p, 1, 1, 0, 1;\n}"
        : "+f"(d[0]), "+f"(d[1]), "+f"(d[2]), "+f"(d[3]), "+f"(d[4]), "+f"(d[5]), "+f"(d[6]), "+f"(d[7]),
          "+f"(d[8]), "+f"(d[9]), "+f"(d[10]), "+f"(d[11]), "+f"(d[12]), "+f"(d[13]), "+f"(d[14]), "+f"(d[15]),
          "+f"(d[16]), "+f"(d[17]), "+f"(d[18]), "+f"(d[19]), "+f"(d[20]), "+f"(d[21]), "+f"(d[22]), "+f"(d[23]),
          "+f"(d[24]), "+f"(d[25]), "+f"(d[26]), "+f"(d[27]), "+f"(d[28]), "+f"(d[29]), "+f"(d[30]), "+f"(d[31]),
          "+f"(d[32]), "+f"(d[33]), "+f"(d[34]), "+f"(d[35]), "+f"(d[36]), "+f"(d[37]), "+f"(d[38]), "+f"(d[39]),
          "+f"(d[40]), "+f"(d[41]), "+f"(d[42]), "+f"(d[43]), "+f"(d[44]), "+f"(d[45]), "+f"(d[46]), "+f"(d[47]),
          "+f"(d[48]), "+f"(d[49]), "+f"(d[50]), "+f"(d[51]), "+f"(d[52]), "+f"(d[53]), "+f"(d[54]), "+f"(d[55]),
          "+f"(d[56]), "+f"(d[57]), "+f"(d[58]), "+f"(d[59]), "+f"(d[60]), "+f"(d[61]), "+f"(d[62]), "+f"(d[63])
        : "r"(da), "r"(db), "r"(scale_d));
}
__device__ __forceinline__ void wgmma_rs_n128_kb(float (&d)[64], uint32_t a0, uint32_t a1, uint32_t a2, uint32_t a3, uint32_t db, int scale_d) {
    asm volatile("{\n.reg .pred p;\n.reg .b64 da, db;\nsetp.ne.b32 p, %69, 0;\n"
        "mov.b64 db, {%68, 0x40000040};\n"
        "wgmma.mma_async.sync.aligned.m64n128k16.f32.bf16.bf16 "
        "{%0, %1, %2, %3, %4, %5, %6, %7, %8, %9, %10, %11, %12, %13, %14, %15, "
        "%16, %17, %18, %19, %20, %21, %22, %23, %24, %25, %26, %27, %28, %29, %30, %31, "
        "%32, %33, %34, %35, %36, %37, %38, %39, %40, %41, %42, %43, %44, %45, %46, %47, "
        "%48, %49, %50, %51, %52, %53, %54, %55, %56, %57, %58, %59, %60, %61, %62, %63}, "
        "{%64, %65, %66, %67}, db, p, 1, 1, 0;\n}"
        : "+f"(d[0]), "+f"(d[1]), "+f"(d[2]), "+f"(d[3]), "+f"(d[4]), "+f"(d[5]), "+f"(d[6]), "+f"(d[7]),
          "+f"(d[8]), "+f"(d[9]), "+f"(d[10]), "+f"(d[11]), "+f"(d[12]), "+f"(d[13]), "+f"(d[14]), "+f"(d[15]),
          "+f"(d[16]), "+f"(d[17]), "+f"(d[18]), "+f"(d[19]), "+f"(d[20]), "+f"(d[21]), "+f"(d[22]), "+f"(d[23]),
          "+f"(d[24]), "+f"(d[25]), "+f"(d[26]), "+f"(d[27]), "+f"(d[28]), "+f"(d[29]), "+f"(d[30]), "+f"(d[31]),
          "+f"(d[32]), "+f"(d[33]), "+f"(d[34]), "+f"(d[35]), "+f"(d[36]), "+f"(d[37]), "+f"(d[38]), "+f"(d[39]),
          "+f"(d[40]), "+f"(d[41]), "+f"(d[42]), "+f"(d[43]), "+f"(d[44]), "+f"(d[45]), "+f"(d[46]), "+f"(d[47]),
          "+f"(d[48]), "+f"(d[49]), "+f"(d[50]), "+f"(d[51]), "+f"(d[52]), "+f"(d[53]), "+f"(d[54]), "+f"(d[55]),
          "+f"(d[56]), "+f"(d[57]), "+f"(d[58]), "+f"(d[59]), "+f"(d[60]), "+f"(d[61]), "+f"(d[62]), "+f"(d[63])
        : "r"(a0), "r"(a1), "r"(a2), "r"(a3), "r"(db), "r"(scale_d));
}
__device__ __forceinline__ void wgmma_rs_n128_tb(float (&d)[64], uint32_t a0, uint32_t a1, uint32_t a2, uint32_t a3, uint32_t db, int scale_d) {
    asm volatile("{\n.reg .pred p;\n.reg .b64 da, db;\nsetp.ne.b32 p, %69, 0;\n"
        "mov.b64 db, {%68, 0x40000040};\n"
        "wgmma.mma_async.sync.aligned.m64n128k16.f32.bf16.bf16 "
        "{%0, %1, %2, %3, %4, %5, %6, %7, %8, %9, %10, %11, %12, %13, %14, %15, "
        "%16, %17, %18, %19, %20, %21, %22, %23, %24, %25, %26, %27, %28, %29, %30, %31, "
        "%32, %33, %34, %35, %36, %37, %38, %39, %40, %41, %42, %43, %44, %45, %46, %47, "
        "%48, %49, %50, %51, %52, %53, %54, %55, %56, %57, %58, %59, %60, %61, %62, %63}, "
        "{%64, %65, %66, %67}, db, p, 1, 1, 1;\n}"
        : "+f"(d[0]), "+f"(d[1]), "+f"(d[2]), "+f"(d[3]), "+f"(d[4]), "+f"(d[5]), "+f"(d[6]), "+f"(d[7]),
          "+f"(d[8]), "+f"(d[9]), "+f"(d[10]), "+f"(d[11]), "+f"(d[12]), "+f"(d[13]), "+f"(d[14]), "+f"(d[15]),
          "+f"(d[16]), "+f"(d[17]), "+f"(d[18]), "+f"(d[19]), "+f"(d[20]), "+f"(d[21]), "+f"(d[22]), "+f"(d[23]),
          "+f"(d[24]), "+f"(d[25]), "+f"(d[26]), "+f"(d[27]), "+f"(d[28]), "+f"(d[29]), "+f"(d[30]), "+f"(d[31]),
          "+f"(d[32]), "+f"(d[33]), "+f"(d[34]), "+f"(d[35]), "+f"(d[36]), "+f"(d[37]), "+f"(d[38]), "+f"(d[39]),
          "+f"(d[40]), "+f"(d[41]), "+f"(d[42]), "+f"(d[43]), "+f"(d[44]), "+f"(d[45]), "+f"(d[46]), "+f"(d[47]),
          "+f"(d[48]), "+f"(d[49]), "+f"(d[50]), "+f"(d[51]), "+f"(d[52]), "+f"(d[53]), "+f"(d[54]), "+f"(d[55]),
          "+f"(d[56]), "+f"(d[57]), "+f"(d[58]), "+f"(d[59]), "+f"(d[60]), "+f"(d[61]), "+f"(d[62]), "+f"(d[63])
        : "r"(a0), "r"(a1), "r"(a2), "r"(a3), "r"(db), "r"(scale_d));
}
__device__ __forceinline__ void wgmma_ss_n192_tb(float (&d)[96], uint32_t da, uint32_t db, int scale_d) {
    asm volatile("{\n.reg .pred p;\n.reg .b64 da, db;\nsetp.ne.b32 p, %98, 0;\n"
        "mov.b64 da, {%96, 0x40000040};\nmov.b64 db, {%97, 0x40000040};\n"
        "wgmma.mma_async.sync.aligned.m64n192k16.f32.bf16.bf16 "
        "{%0, %1, %2, %3, %4, %5, %6, %7, %8, %9, %10, %11, %12, %13, %14, %15, "
        "%16, %17, %18, %19, %20, %21, %22, %23, %24, %25, %26, %27, %28, %29, %30, %31, "
        "%32, %33, %34, %35, %36, %37, %38, %39, %40, %41, %42, %43, %44, %45, %46, %47, "
        "%48, %49, %50, %51, %52, %53, %54, %55, %56, %57, %58, %59, %60, %61, %62, %63, "
        "%64, %65, %66, %67, %68, %69, %70, %71, %72, %73, %74, %75, %76, %77, %78, %79, "
        "%80, %81, %82, %83, %84, %85, %86, %87, %88, %89, %90, %91, %92, %93, %94, %95}, "
        "da, db, p, 1, 1, 0, 1;\n}"
        : "+f"(d[0]), "+f"(d[1]), "+f"(d[2]), "+f"(d[3]), "+f"(d[4]), "+f"(d[5]), "+f"(d[6]), "+f"(d[7]),
          "+f"(d[8]), "+f"(d[9]), "+f"(d[10]), "+f"(d[11]), "+f"(d[12]), "+f"(d[13]), "+f"(d[14]), "+f"(d[15]),
          "+f"(d[16]), "+f"(d[17]), "+f"(d[18]), "+f"(d[19]), "+f"(d[20]), "+f"(d[21]), "+f"(d[22]), "+f"(d[23]),
          "+f"(d[24]), "+f"(d[25]), "+f"(d[26]), "+f"(d[27]), "+f"(d[28]), "+f"(d[29]), "+f"(d[30]), "+f"(d[31]),
          "+f"(d[32]), "+f"(d[33]), "+f"(d[34]), "+f"(d[35]), "+f"(d[36]), "+f"(d[37]), "+f"(d[38]), "+f"(d[39]),
          "+f"(d[40]), "+f"(d[41]), "+f"(d[42]), "+f"(d[43]), "+f"(d[44]), "+f"(d[45]), "+f"(d[46]), "+f"(d[47]),
          "+f"(d[48]), "+f"(d[49]), "+f"(d[50]), "+f"(d[51]), "+f"(d[52]), "+f"(d[53]), "+f"(d[54]), "+f"(d[55]),
          "+f"(d[56]), "+f"(d[57]), "+f"(d[58]), "+f"(d[59]), "+f"(d[60]), "+f"(d[61]), "+f"(d[62]), "+f"(d[63]),
          "+f"(d[64]), "+f"(d[65]), "+f"(d[66]), "+f"(d[67]), "+f"(d[68]), "+f"(d[69]), "+f"(d[70]), "+f"(d[71]),
          "+f"(d[72]), "+f"(d[73]), "+f"(d[74]), "+f"(d[75]), "+f"(d[76]), "+f"(d[77]), "+f"(d[78]), "+f"(d[79]),
          "+f"(d[80]), "+f"(d[81]), "+f"(d[82]), "+f"(d[83]), "+f"(d[84]), "+f"(d[85]), "+f"(d[86]), "+f"(d[87]),
          "+f"(d[88]), "+f"(d[89]), "+f"(d[90]), "+f"(d[91]), "+f"(d[92]), "+f"(d[93]), "+f"(d[94]), "+f"(d[95])
        : "r"(da), "r"(db), "r"(scale_d));
}

#define PRAGMA_(x) _Pragma(#x)
#define UNROLL(n) PRAGMA_(unroll n)
template <int V> struct IC { static constexpr int value = V; };
template <int B, int E, class F> __device__ __forceinline__ void static_for(F&& f) {
    if constexpr (B < E) { f(IC<B>{}); static_for<B + 1, E>(f); }
}

constexpr float QSCALE = 0.08838834764831845f * 1.4426950408889634f;
#define G_PBASE0 1
#define G_PSTEP 1
constexpr int HELP_UNIT = 26;
constexpr int PROG_OFF = 520;
constexpr int PSLAB = 5 * 256 * 16;
constexpr int XS_OFF = 7 * PSLAB;

__device__ __forceinline__ void store_tile128(__nv_bfloat16* rowp  , size_t row8_stride,
                                              const float (&a)[64], float s0, float s1) {
#pragma unroll
    for (int m = 0; m < 4; m++) {
        uint4 v0, v1;
        v0.x = pack_bf16(a[16 * m + 0] * s0, a[16 * m + 1] * s0);
        v0.y = pack_bf16(a[16 * m + 4] * s0, a[16 * m + 5] * s0);
        v0.z = pack_bf16(a[16 * m + 8] * s0, a[16 * m + 9] * s0);
        v0.w = pack_bf16(a[16 * m + 12] * s0, a[16 * m + 13] * s0);
        v1.x = pack_bf16(a[16 * m + 2] * s1, a[16 * m + 3] * s1);
        v1.y = pack_bf16(a[16 * m + 6] * s1, a[16 * m + 7] * s1);
        v1.z = pack_bf16(a[16 * m + 10] * s1, a[16 * m + 11] * s1);
        v1.w = pack_bf16(a[16 * m + 14] * s1, a[16 * m + 15] * s1);
        *reinterpret_cast<uint4*>(rowp + 32 * m) = v0;
        *reinterpret_cast<uint4*>(rowp + row8_stride + 32 * m) = v1;
    }
}

template <int PIECE>
__device__ __forceinline__ void g_epi_piece(const float (&a)[64], int type, __nv_bfloat16* dst, int row8_stride, float rs0, float rs1) {
    asm volatile("" : "+f"(rs0), "+f"(rs1));
    if (type == 1) {
        constexpr int m = PIECE >> 1, rh = PIECE & 1;
        const float cexp = (rh ? rs1 : rs0) * -1.4426950408889634f;
        uint32_t o[4];
#pragma unroll
        for (int jj = 0; jj < 4; jj++) {
            const int gi = 16 * m + 4 * jj + 2 * rh;
            const uint32_t sg = pack_bf16(rcp(1.0f + ex2(a[gi] * cexp)), rcp(1.0f + ex2(a[gi + 1] * cexp)));
            o[jj] = hmul2_bf16(hmul2_bf16(pack_bf16(a[gi], a[gi + 1]), sg), pack_bf16(a[32 + gi], a[32 + gi + 1]));
        }
        *reinterpret_cast<uint4*>(dst + rh * row8_stride + 32 * m) = make_uint4(o[0], o[1], o[2], o[3]);
    } else if (type == 2) {
        constexpr int m = PIECE;
        uint4 v0, v1;
        rs0 *= QSCALE; rs1 *= QSCALE;
        v0.x = pack_bf16(a[16 * m + 0] * rs0, a[16 * m + 1] * rs0);
        v0.y = pack_bf16(a[16 * m + 2] * rs1, a[16 * m + 3] * rs1);
        v0.z = pack_bf16(a[16 * m + 4] * rs0, a[16 * m + 5] * rs0);
        v0.w = pack_bf16(a[16 * m + 6] * rs1, a[16 * m + 7] * rs1);
        v1.x = pack_bf16(a[16 * m + 8] * rs0, a[16 * m + 9] * rs0);
        v1.y = pack_bf16(a[16 * m + 10] * rs1, a[16 * m + 11] * rs1);
        v1.z = pack_bf16(a[16 * m + 12] * rs0, a[16 * m + 13] * rs0);
        v1.w = pack_bf16(a[16 * m + 14] * rs1, a[16 * m + 15] * rs1);
        *reinterpret_cast<uint4*>(dst + 32 * m) = v0;
        *reinterpret_cast<uint4*>(dst + row8_stride + 32 * m) = v1;
    }
}

struct GCtx {
    uint32_t a_lo, b_lo;
    uint32_t bars;
    int sg;
    float rs0, rs1;
    uint32_t lane0, ready, relprev;
    int pbase;
    uint32_t rbars, el;
};

__device__ __forceinline__ void g_stage(float (&acc)[64], GCtx& c, int kb, int accumulate) {
    const int s = c.sg & 3;
    if (!__all_sync(0xffffffffu, c.ready)) {
        mbar_wait_u(c.bars + (B_FULLG + s) * 8, (c.sg >> 2) & 1);
    }
    const uint32_t da = c.a_lo + kb * (SLOT >> 4);
    const uint32_t db = c.b_lo + s * (SLOT >> 4);
    wgmma_fence();
#pragma unroll
    for (int kk = 0; kk < 4; kk++)
        wgmma_ss_n128_tb(acc, da + kk * 2, db + kk * 128, kk != 0 ? 1 : accumulate);
    wgmma_commit();
    c.sg++;
    c.ready = mbar_probe(c.bars + (B_FULLG + (c.sg & 3)) * 8, (c.sg >> 2) & 1);
    wgmma_wait<1>();
    mbar_arrive_remote_if(c.rbars + (B_EMPTYG + ((c.sg - 2) & 3)) * 8, c.relprev);
    c.relprev = c.el;
}
__device__ __forceinline__ void g_tile(float (&acc)[64], float (&prev)[64], int ptype, __nv_bfloat16* pdst, int pstride,
                                       GCtx& c, uint32_t pub_bar) {
    g_stage(acc, c, 0, 0);
    fence_regs(prev);
#define G_UNROLL 1
    UNROLL(G_UNROLL)
    for (int kb = 1; kb < 10; kb++) {
        g_stage(acc, c, kb, 1);
        const int pc = ((kb - c.pbase) & 1) ? -1 : (kb - c.pbase) >> 1;
        if (pc == 0) g_epi_piece<0>(prev, ptype, pdst, pstride, c.rs0, c.rs1);
        else if (pc == 1) g_epi_piece<1>(prev, ptype, pdst, pstride, c.rs0, c.rs1);
        else if (pc == 2) g_epi_piece<2>(prev, ptype, pdst, pstride, c.rs0, c.rs1);
        else if (pc == 3) {
            g_epi_piece<3>(prev, ptype, pdst, pstride, c.rs0, c.rs1);
            mbar_arrive_warp(pub_bar, pub_bar && c.lane0);
        }
    }
}

template <int SET>
__global__ void __launch_bounds__(384, 1)
fused_kernel(const __grid_constant__ CUtensorMap tm_w1, const __grid_constant__ CUtensorMap tm_w3,
             const __grid_constant__ CUtensorMap tm_wq, const __grid_constant__ CUtensorMap tm_k,
             const __grid_constant__ CUtensorMap tm_v, const __grid_constant__ CUtensorMap tm_wo,
             const __grid_constant__ CUtensorMap tm_w2, const __grid_constant__ CUtensorMap tm_o,
             const __grid_constant__ CUtensorMap tm_h, const __grid_constant__ CUtensorMap tm_x,
             const __grid_constant__ CUtensorMap tm_out, const __grid_constant__ CUtensorMap tm_xs) {
    extern __shared__ __align__(1024) uint8_t smem_raw[];
    const uint32_t sbase = (smem_u32(smem_raw) + 1023) & ~1023u;
    const uint32_t bars = sbase + OFF_BAR;
    const int tid = threadIdx.x;
    const int warp = __shfl_sync(0xffffffffu, tid >> 5, 0);
    const int wg = warp >> 2;
    const int lane = tid & 31;
    const uint32_t rank = cluster_ctarank();
    const int cl = blockIdx.x >> 1;
    const bool helper = SET && cl >= 64;
    const int g = cl & 7;
    const int pr = cl >> 3;
    const int t = (helper ? (cl - 64) * 4 : pr) * 2 + (int)rank;
    const int nunits = (PK_UNITS[SET] >> (4 * g)) & 15;
    const int ntiles = nunits + 4;
    const int ustart = (int)((PK_USTART[SET] >> (8 * g)) & 255);
    const int nblk = (int)((PK_NBLK[SET] >> (8 * g)) & 255);
    unsigned* cnt = g_cnt + t * 128;

    if (tid == 0) {
        for (int i = 0; i < 10; i++) mbar_init(bars + (B_X + i) * 8, 1);
        asm volatile("fence.mbarrier_init.release.cluster;" ::: "memory");
        if (!helper) {
            for (int i = 0; i < 10; i++) {
                mbar_expect_tx(bars + (B_X + i) * 8, SLOT);
                tma_2d(sbase + i * SLOT, &tm_x, i * 64, t * 128, bars + (B_X + i) * 8);
            }
        }
    } else if (tid == 64) {
        for (int i = 0; i < 4; i++) { mbar_init(bars + (B_FULLG + i) * 8, 1); mbar_init(bars + (B_EMPTYG + i) * 8, 4); }
        for (int i = 0; i < NP + 2; i++) { mbar_init(bars + (B_FULLA + i) * 8, 1); mbar_init(bars + (B_EMPTYA + i) * 8, 4); }
        for (int i = 0; i < 4; i++) { mbar_init(bars + (B_FULL3 + i) * 8, 1); mbar_init(bars + (B_EMPTY3 + i) * 8, 4); }
        mbar_init(bars + B_XNFREE * 8, 4);
        for (int i = 0; i < 8; i++) mbar_init(bars + (B_PUB + i) * 8, 8);
        for (int i = 0; i < 3; i++) mbar_init(bars + (B_IN + i) * 8, 1);
        mbar_init(bars + B_XS * 8, 1);
        mbar_init(bars + B_FREE * 8, 1);
        asm volatile("st.volatile.shared.s32 [%0], %1;" :: "r"(bars + PROG_OFF), "r"(0) : "memory");
        asm volatile("fence.mbarrier_init.release.cluster;" ::: "memory");
    } else if (tid == 32) {
        prefetch_tmap(&tm_w1); prefetch_tmap(&tm_w3); prefetch_tmap(&tm_wq); prefetch_tmap(&tm_k); prefetch_tmap(&tm_v);
        prefetch_tmap(&tm_wo); prefetch_tmap(&tm_w2); prefetch_tmap(&tm_o); prefetch_tmap(&tm_h);
    }
    __syncthreads();
    cluster_arrive_relaxed();

    if (wg == 2) {
        asm volatile("setmaxnreg.dec.sync.aligned.u32 40;");
        cluster_wait();
        const unsigned epoch = (*(volatile unsigned*)cnt) >> 3;
        auto recv_partial = [&](int d) {
            const int nh = g & 1, kq = g >> 1;
            const int src = d < kq ? d : d + 1;
            wait_flag(cnt + 64 + nh * 16 + kq * 4 + src, epoch + 1, 22);
            if (src == 3) {
                asm volatile("fence.proxy.async;" ::: "memory");
                mbar_expect_tx(bars + (B_IN + d) * 8, PSLAB);
                bulk_load(sbase + (4 + d) * PSLAB, g_part + (size_t)(((t * 2 + nh) * 4 + src) * 4 + kq) * (PSLAB / 16), PSLAB, bars + (B_IN + d) * 8);
            } else {
                mbar_arrive(bars + (B_IN + d) * 8);
            }
        };
        if (helper) {
            if (warp == 8 && lane == 0) {
                int sg = 0;
                for (int r = 0; r < 4; r++) {
                    if (r > 0) mbar_wait(bars + B_XNFREE * 8, (r - 1) & 1, 12);
                    else __nanosleep(3000);
                    {
                        for (int i = 0; i < 10; i++) {
                            mbar_expect_tx(bars + (B_X + i) * 8, SLOT);
                            tma_2d(sbase + i * SLOT, &tm_x, i * 64, (t + 2 * r) * 128, bars + (B_X + i) * 8);
                        }
                    }
                    for (int kb = 0; kb < 10; kb++, sg++) {
                        const int s = sg & 3;
                        mbar_wait(bars + (B_EMPTYG + s) * 8, ((sg >> 2) & 1) ^ 1, 10);
                        mbar_expect_tx(bars + (B_FULLG + s) * 8, SLOT);
                        tma_2d_mc(sbase + OFF_RINGG + s * SLOT + rank * 8192, rank ? &tm_w3 : &tm_w1, HELP_UNIT * 64, kb * 64, bars + (B_FULLG + s) * 8);
                    }
                }
                for (int v = 0; v < 4; v++, sg++) mbar_wait(bars + (B_EMPTYG + (sg & 3)) * 8, ((sg >> 2) & 1) ^ 1, 10);
                mbar_wait(bars + B_XNFREE * 8, 1, 12);
            } else if (warp == 9 && lane == 0) {
                for (int r = 0; r < 4; r++) {
                    mbar_wait(bars + (B_PUB + r) * 8, 0, 30);
                    asm volatile("fence.proxy.async;" ::: "memory");
                    __threadfence();
                    red_release(g_cnt + (t + 2 * r) * 128 + 4, 1);
                }
            }
        } else if (warp == 8 && lane == 0) {
            const int nh = g & 1, kq = g >> 1;
            const CUtensorMap* mb = (kq == 3) ? &tm_w2 : &tm_wo;
            auto progress = [&](int v) { asm volatile("st.volatile.shared.s32 [%0], %1;" :: "r"(bars + PROG_OFF), "r"(v) : "memory"); };
            mbar_wait(bars + (B_X + 5) * 8, 0, 9);
            int sg = 0;
            for (int tile = 0; tile < ntiles; tile++) {
                const CUtensorMap* m = tile < nunits ? (rank ? &tm_w3 : &tm_w1) : &tm_wq;
                const int c0 = tile < nunits ? (ustart + tile) * 64 : (4 * g + ((tile - nunits + 1) & 3)) * 128 + rank * 64;
#pragma unroll 2
                for (int kb = 0; kb < 10; kb++, sg++) {
                    const int s = sg & 3;
                    mbar_wait(bars + (B_EMPTYG + s) * 8, ((sg >> 2) & 1) ^ 1, 10);
                    mbar_expect_tx(bars + (B_FULLG + s) * 8, SLOT);
                    tma_2d_mc(sbase + OFF_RINGG + s * SLOT + rank * 8192, m, c0, kb * 64, bars + (B_FULLG + s) * 8);
                    progress(sg);
                }
            }
            int sa = 0, pa = 0;
            for (int T = 0; T < 32; T++) {
                const bool isv = T == 31 || (T >= 2 && !(T & 1));
                const int blk = T == 31 ? 15 : (T < 2 ? T : (isv ? (T - 2) >> 1 : (T + 1) >> 1));
                const int kv0 = (4 * g + (blk >> 2)) * SKV + KOFF + (blk & 3) * 128;
                const CUtensorMap* m = isv ? &tm_v : &tm_k;
                const int c0 = isv ? rank * 64 : 0, c1 = isv ? kv0 : kv0 + rank * 64;
                const int dc0 = isv ? 0 : 64, dc1 = isv ? 64 : 0;
                uint32_t dst, fb;
                if (T < 2) {
                    for (int v = 0; v < 2; v++) mbar_wait(bars + (B_EMPTYG + ((sg + v) & 3)) * 8, (((sg + v) >> 2) & 1) ^ 1, 11);
                    dst = sbase + OFF_RINGG + (sg & 3) * SLOT; fb = bars + (B_FULLA + NP + T) * 8;
                    sg += 2;
                } else {
                    dst = sbase + sa * 2 * SLOT; fb = bars + (B_FULLA + sa) * 8;
                    if (T == 2) mbar_wait(bars + B_XNFREE * 8, 0, 12);
                    if (T >= 2 + NP) mbar_wait(bars + (B_EMPTYA + sa) * 8, pa ^ 1, 13);
                    if (++sa == NP) { sa = 0; pa ^= 1; }
                }
                mbar_expect_tx(fb, 2 * SLOT);
                tma_2d_mc(dst + rank * 8192, m, c0, c1, fb);
                tma_2d_mc(dst + SLOT + rank * 8192, m, c0 + dc0, c1 + dc1, fb);
                progress(10 * ntiles + 2 * T + 1);
            }
            const CUtensorMap* ma = (kq == 3) ? &tm_h : &tm_o;
            int round_ok = -1;
            for (int i = 0; i < nblk; i++) {
                const int st = i & 3;
                if (i == 0) { mbar_wait(bars + (B_EMPTYA + NP) * 8, 0, 14); mbar_wait(bars + (B_EMPTYA + NP + 1) * 8, 0, 14); }
                else if (i == 1) { mbar_wait(bars + (B_EMPTYA + 0) * 8, pa ^ 1, 15); mbar_wait(bars + (B_EMPTYA + 1) * 8, pa ^ 1, 15); }
                else if (i == 2) { mbar_wait(bars + (B_EMPTYA + 2) * 8, pa ^ 1, 15); mbar_wait(bars + (B_EMPTYA + 3) * 8, pa ^ 1, 15); }
                else if (i == 3) mbar_wait(bars + (B_EMPTYA + 4) * 8, pa ^ 1, 15);
                else mbar_wait(bars + (B_EMPTY3 + st) * 8, ((i >> 2) & 1) ^ 1, 18);
                const int b = c_blk[SET][g][i];
                const int round = (kq == 3) ? 0 : ((b >> 1) & 3);
                if (SET && kq == 3 && b == HELP_UNIT) {
                    wait_flag(cnt + 4, epoch + 1, 19);
                    asm volatile("fence.proxy.async;" ::: "memory");
                }
                if (round != round_ok) {
                    if (kq == 3) wait_flag(cnt, (epoch + 1) * 8, 19);
                    else wait_flag(cnt + 8 + round * 8, (epoch + 1) * 8, 20);
                    asm volatile("fence.proxy.async;" ::: "memory");
                    round_ok = round;
                }
                const uint32_t base = sbase + ((st + 3) & 3) * ST3;
                const uint32_t fb = bars + (B_FULL3 + st) * 8;
                mbar_expect_tx(fb, ST3);
                tma_5d_mc(base + SLOT + rank * 20480, mb, b * 8 + rank * 4, nh * 5, fb);
                tma_2d(base, ma, b * 64, t * 128, fb);
                progress(10 * ntiles + 64 + i);
            }
            progress(1 << 20);
            for (int i = nblk; i < nblk + 4; i++)
                mbar_wait(bars + (B_EMPTY3 + (i & 3)) * 8, ((i >> 2) & 1) ^ 1, 21);
            mbar_arrive(bars + B_FREE * 8);
            mbar_expect_tx(bars + B_XS * 8, PSLAB);
            tma_2d(sbase + XS_OFF, &tm_xs, nh * 320 + kq * 80, t * 128, bars + B_XS * 8);
            tma_2d(sbase + XS_OFF + PSLAB / 2, &tm_xs, nh * 320 + kq * 80 + 40, t * 128, bars + B_XS * 8);
            recv_partial(0);
        } else if (warp >= 10) {
            if (warp == 10) {
                for (int it = 0; it <= 16; it++) {
                    if (it < 2) mbar_wait_u(bars + (B_FULLA + NP + it) * 8, 0);
                    else if (it < 16) { const int m = 2 * it - 3; mbar_wait_u(bars + (B_FULLA + m % NP) * 8, (m / NP) & 1); }
                    if (it > 0) { const int m = it < 16 ? 2 * it - 2 : 29; mbar_wait_u(bars + (B_FULLA + m % NP) * 8, (m / NP) & 1); }
                    named_sync(1, 288);
                    named_sync(2, 288);
                }
            }
            if (warp == 11 && lane == 0) {
                const int nG = 10 * ntiles, nh = g & 1, kq = g >> 1;
                auto prefetch = [&](int s) {
                    if (s < nG) {
                        const int tile = s / 10, kb = s - tile * 10;
                        if (tile < nunits) prefetch_2d(rank ? &tm_w3 : &tm_w1, (ustart + tile) * 64, kb * 64);
                        else prefetch_2d(&tm_wq, (4 * g + ((tile - nunits + 1) & 3)) * 128 + rank * 64, kb * 64);
                    } else if (s < nG + 64) {
                        const int T = (s - nG) >> 1, half = (s - nG) & 1;
                        const bool isv = T == 31 || (T >= 2 && !(T & 1));
                        const int blk = T == 31 ? 15 : (T < 2 ? T : (isv ? (T - 2) >> 1 : (T + 1) >> 1));
                        const int kv0 = (4 * g + (blk >> 2)) * SKV + KOFF + (blk & 3) * 128;
                        if (isv) prefetch_2d(&tm_v, rank * 64, kv0 + half * 64);
                        else prefetch_2d(&tm_k, half * 64, kv0 + rank * 64);
                    } else if (s - (nG + 64) < nblk) {
                        prefetch_5d((kq == 3) ? &tm_w2 : &tm_wo, c_blk[SET][g][s - (nG + 64)] * 8 + rank * 4, nh * 5);
                    }
                };
#define PF_DIST 10
                mbar_wait(bars + (B_X + 5) * 8, 0, 9);
#pragma unroll 1
                for (int s = pr < 4 ? pr + 8 : pr; s < nG + 64 + nblk; s += 8) {
                    unsigned n = 0;
                    int cur;
                    do {
                        asm volatile("ld.volatile.shared.s32 %0, [%1];" : "=r"(cur) : "r"(bars + PROG_OFF) : "memory");
                        if (cur + PF_DIST >= s) break;
                        __nanosleep(64);
                    } while (++n < (1u << 24));
                    prefetch(s);
                }
            }
            if (lane == 0) {
                mbar_wait(bars + B_FREE * 8, 0, 21);
                recv_partial(warp - 9);
            }
        } else if (warp == 9 && lane == 0) {
            for (int ev = 0; ev < 5; ev++) {
                mbar_wait(bars + (B_PUB + ev) * 8, 0, 30);
                asm volatile("fence.proxy.async;" ::: "memory");
                __threadfence();
                red_release(ev == 0 ? cnt : cnt + 8 * ev, 1);
            }
            {
                const int nh = g & 1, kq = g >> 1;
                mbar_wait(bars + (B_PUB + 5) * 8, 0, 31);
                unsigned* fl = cnt + 64 + nh * 16 + kq;
                asm volatile("fence.proxy.async;" ::: "memory");
                asm volatile("fence.acq_rel.gpu;" ::: "memory");
                for (int d = 1; d < 4; d++)
                    asm volatile("red.relaxed.gpu.global.add.u32 [%0], %1;" :: "l"(fl + ((kq + d) & 3) * 4), "r"(1u) : "memory");
            }
        }
    } else {
        asm volatile("setmaxnreg.inc.sync.aligned.u32 232;");
        const int wl = warp & 3;
        const int q4 = lane & 3;
        const uint32_t el = ((tid & 127) == 0 || (tid & 127) == 32) ? 1u : 0u;
        const uint32_t rbars = mapa_u32(bars, (tid & 127) == 32 ? 1u : 0u);
        const int row0 = t * 128 + wg * 64 + wl * 16 + (lane >> 2);

        float rs0, rs1;
        GCtx c;
        uint32_t qf[32];
        {
            float accA[64], accB[64];
            c.sg = 0;
#pragma unroll 1
            for (int r = 0;; r++) {
            const int g8 = lane >> 2;
            const int ra = wg * 64 + wl * 16 + g8;
            uint32_t xa[80], xb[80];
            float sm[2][4] = {{0.f, 0.f, 0.f, 0.f}, {0.f, 0.f, 0.f, 0.f}};
            float ga[2][4] = {{0.f, 0.f, 0.f, 0.f}, {0.f, 0.f, 0.f, 0.f}}, gb[2][4] = {{0.f, 0.f, 0.f, 0.f}, {0.f, 0.f, 0.f, 0.f}};
            uint32_t sha = 0, shb = 0;
#pragma unroll
            for (int m = 0; m < 10; m++) {
                mbar_wait_u(bars + (B_X + m) * 8, r & 1);
#pragma unroll
                for (int ii = 0; ii < 2; ii++) {
                    const int i = 2 * m + ii;
                    const int c = q4 + 4 * (i ^ (g8 & 1));
                    const uint32_t src = sbase + m * SLOT + ra * 128 + (((c & 7) ^ (ra & 7)) << 4);
                    asm volatile("ld.shared.v4.b32 {%0, %1, %2, %3}, [%4];" : "=r"(xa[4 * i]), "=r"(xa[4 * i + 1]), "=r"(xa[4 * i + 2]), "=r"(xa[4 * i + 3]) : "r"(src) : "memory");
                    asm volatile("ld.shared.v4.b32 {%0, %1, %2, %3}, [%4];" : "=r"(xb[4 * i]), "=r"(xb[4 * i + 1]), "=r"(xb[4 * i + 2]), "=r"(xb[4 * i + 3]) : "r"(src + 8 * 128) : "memory");
                }
                if (m == 0) {
                    const uint32_t ea = (g8 & 1) ? xa[4] : xa[0], eb = (g8 & 1) ? xb[4] : xb[0];
                    sha = __shfl_sync(0xffffffffu, ea, lane & ~3); shb = __shfl_sync(0xffffffffu, eb, lane & ~3);
                    sha = __byte_perm(sha, sha, 0x1010); shb = __byte_perm(shb, shb, 0x1010);
                }
#pragma unroll
                for (int u = 0; u < 4; u++) {
                    const int e = 8 * m + 2 * u;
                    const uint32_t a0 = hsub2_bf16(xa[e], sha), a2 = hsub2_bf16(xa[e + 1], sha);
                    const uint32_t a1 = hsub2_bf16(xb[e], shb), a3 = hsub2_bf16(xb[e + 1], shb);
                    mma_bf16(sm[u & 1], a0, a1, a2, a3, 0x3F803F80u, 0x3F803F80u);
                    mma_bf16(ga[u & 1], a0, a1, a2, a3, a0, a2);
                    mma_bf16(gb[u & 1], a0, a1, a2, a3, a1, a3);
                }
            }
            const float ea1 = (sm[0][0] + sm[1][0]) * (1.0f / DM), eb1 = (sm[0][2] + sm[1][2]) * (1.0f / DM);
            const float mean_a = bf_lo(sha) + ea1, mean_b = bf_lo(shb) + eb1;
            const uint32_t mab = pack_bf16(mean_a, mean_b);
            const uint32_t ma2 = __byte_perm(mab, mab, 0x1010), mb2 = __byte_perm(mab, mab, 0x3232);
            const int dl = 4 * g8 + (g8 >> 1);
            const float sqa = __shfl_sync(0xffffffffu, (g8 & 1) ? ga[0][1] + ga[1][1] : ga[0][0] + ga[1][0], dl);
            const float sqb = __shfl_sync(0xffffffffu, (g8 & 1) ? gb[0][3] + gb[1][3] : gb[0][2] + gb[1][2], dl);
            const float var_a = bf_round(fmaxf(sqa * (1.0f / DM) - ea1 * ea1, 0.f));
            const float var_b = bf_round(fmaxf(sqb * (1.0f / DM) - eb1 * eb1, 0.f));
            const float inv_a = 1.0f / bf_round(sqrtf(bf_round(var_a + 1e-5f)));
            const float inv_b = 1.0f / bf_round(sqrtf(bf_round(var_b + 1e-5f)));
            rs0 = inv_a; rs1 = inv_b;
            auto centre = [&](auto M_) {
#pragma unroll
                for (int ii = 0; ii < 2; ii++) {
                    constexpr int m = decltype(M_)::value;
                    const int i = 2 * m + ii;
                    uint32_t oa[4], ob[4];
#pragma unroll
                    for (int e = 0; e < 4; e++) {
                        oa[e] = hsub2_bf16(xa[4 * i + e], ma2);
                        ob[e] = hsub2_bf16(xb[4 * i + e], mb2);
                    }
                    const int cc = q4 + 4 * (i ^ (g8 & 1));
                    const uint32_t dst = sbase + m * SLOT + ra * 128 + (((cc & 7) ^ (ra & 7)) << 4);
                    asm volatile("st.shared.v4.b32 [%0], {%1, %2, %3, %4};" :: "r"(dst), "r"(oa[0]), "r"(oa[1]), "r"(oa[2]), "r"(oa[3]) : "memory");
                    asm volatile("st.shared.v4.b32 [%0], {%1, %2, %3, %4};" :: "r"(dst + 8 * 128), "r"(ob[0]), "r"(ob[1]), "r"(ob[2]), "r"(ob[3]) : "memory");
                }
            };
            static_for<0, 4>([&](auto M_) { centre(M_); });
            asm volatile("fence.proxy.async.shared::cta;" ::: "memory");
            named_sync(3 + wg, 128);
            if (r == 0) cluster_wait();
            c.a_lo = desc_lo(sbase + wg * 8192, 16); c.b_lo = desc_lo(sbase + OFF_RINGG, 8192); c.bars = bars; c.rbars = rbars; c.el = el;
            c.rs0 = rs0; c.rs1 = rs1; c.lane0 = lane == 0; c.ready = 0; c.relprev = 0; c.pbase = G_PBASE0 + G_PSTEP * wg;
            g_stage(accA, c, 0, 0);
            centre(IC<4>{}); centre(IC<5>{});
            g_stage(accA, c, 1, 1);
            centre(IC<6>{}); centre(IC<7>{});
            g_stage(accA, c, 2, 1);
            centre(IC<8>{}); centre(IC<9>{});
            asm volatile("fence.proxy.async.shared::cta;" ::: "memory");
            g_stage(accA, c, 3, 1);
            named_sync(3 + wg, 128);
#pragma unroll 1
            for (int kb = 4; kb < 10; kb++) g_stage(accA, c, kb, 1);
            if (!helper) break;
            wgmma_wait<0>();
            fence_regs(accA);
            mbar_arrive_remote_if(rbars + (B_EMPTYG + ((c.sg - 1) & 3)) * 8, el);
            mbar_arrive_remote_if(rbars + B_XNFREE * 8, el);
            {
                __nv_bfloat16* const hd = g_h + (size_t)(row0 + r * 256) * FF + 8 * q4 + HELP_UNIT * 64;
                g_epi_piece<0>(accA, 1, hd, 8 * FF, rs0, rs1); g_epi_piece<1>(accA, 1, hd, 8 * FF, rs0, rs1);
                g_epi_piece<2>(accA, 1, hd, 8 * FF, rs0, rs1); g_epi_piece<3>(accA, 1, hd, 8 * FF, rs0, rs1);
                mbar_arrive_warp(bars + (B_PUB + r) * 8, lane == 0);
            }
            if (r == 3) return;
            }
            __nv_bfloat16* const hrow = g_h + (size_t)row0 * FF + 8 * q4;
            __nv_bfloat16* const qrow = g_oq + (size_t)row0 * (NH * DH) + 8 * q4;
            auto epi_type = [&](int i) { return i < nunits ? 1 : 2; };
            auto epi_dst = [&](int i) {
                return i < nunits ? hrow + (ustart + i) * 64 : qrow + (4 * g + ((i - nunits + 1) & 3)) * 128;
            };
            auto epi_stride = [&](int i) { return i < nunits ? 8 * FF : 8 * NH * DH; };
            auto epi_pub = [&](int i) { return (i == nunits - 1) ? bars + B_PUB * 8 : 0u; };
            if (ntiles & 1) {
                wgmma_wait<0>();
                fence_regs(accA);
#pragma unroll
                for (int i = 0; i < 64; i++) accB[i] = accA[i];
            } else {
#pragma unroll
                for (int i = 0; i < 64; i++) asm volatile("" : "=f"(accB[i]));
            }
#pragma unroll 1
            for (int i = (ntiles & 1) ? 1 : 0; i < ntiles; i += 2) {
                if (i > 0) g_tile(accA, accB, epi_type(i - 1), epi_dst(i - 1), epi_stride(i - 1), c, epi_pub(i - 1));
                g_tile(accB, accA, epi_type(i), epi_dst(i), epi_stride(i), c, epi_pub(i));
            }
            wgmma_wait<0>();
            fence_regs(accB);
            mbar_arrive_remote_if(rbars + (B_EMPTYG + ((c.sg - 1) & 3)) * 8, el);
            mbar_arrive_remote_if(rbars + B_XNFREE * 8, el);
#pragma unroll
            for (int j = 0; j < 16; j++) {
                qf[2 * j] = pack_bf16(accB[4 * j] * (rs0 * QSCALE), accB[4 * j + 1] * (rs0 * QSCALE));
                qf[2 * j + 1] = pack_bf16(accB[4 * j + 2] * (rs1 * QSCALE), accB[4 * j + 3] * (rs1 * QSCALE));
            }
        }

        {
            float sacc[64], oacc[64];
            uint32_t pf[32];
            float m0 = 0.f, m1 = 0.f, l0 = 0.f, l1 = 0.f, sc0 = 1.f, sc1 = 1.f, pl0 = 0.f, pl1 = 0.f;
            bool gen = false;
            auto rel = [&](uint32_t idx) { mbar_arrive_remote_if(rbars + idx * 8, el); };
#define WAITA2(a, b, c, d) mbar_wait2(a, b, c, d)
            int sa = 0;
            uint32_t pa = 0;
            auto adv = [&]() { const bool w = sa == NP - 1; sa = w ? 0 : sa + 1; pa ^= w ? 1u : 0u; };

            auto issue_qk = [&](uint32_t a0, uint32_t a1) {
                wgmma_fence();
#pragma unroll
                for (int kk = 0; kk < 4; kk++)
                    wgmma_rs_n128_kb(sacc, qf[4 * kk], qf[4 * kk + 1], qf[4 * kk + 2], qf[4 * kk + 3], a0 + kk * 2, kk != 0);
#pragma unroll
                for (int kk = 4; kk < 8; kk++)
                    wgmma_rs_n128_kb(sacc, qf[4 * kk], qf[4 * kk + 1], qf[4 * kk + 2], qf[4 * kk + 3], a1 + (kk - 4) * 2, 1);
                wgmma_commit();
            };
            auto issue_pv = [&](uint32_t a0, uint32_t a1, int acc_flag) {
                a0 = desc_lo(a0, 8192); a1 = desc_lo(a1, 8192);
                wgmma_fence();
#pragma unroll
                for (int kk = 0; kk < 4; kk++)
                    wgmma_rs_n128_tb(oacc, pf[4 * kk], pf[4 * kk + 1], pf[4 * kk + 2], pf[4 * kk + 3], a0 + kk * 128, kk != 0 ? 1 : acc_flag);
#pragma unroll
                for (int kk = 4; kk < 8; kk++)
                    wgmma_rs_n128_tb(oacc, pf[4 * kk], pf[4 * kk + 1], pf[4 * kk + 2], pf[4 * kk + 3], a1 + (kk - 4) * 128, 1);
                wgmma_commit();
            };
            auto rowmax = [&](float& x0, float& x1) {
                float a[4], b[4];
#pragma unroll
                for (int u = 0; u < 4; u++) {
                    a[u] = fmaxf(sacc[4 * u], sacc[4 * u + 1]);
                    b[u] = fmaxf(sacc[4 * u + 2], sacc[4 * u + 3]);
                }
#pragma unroll
                for (int j = 4; j < 16; j++) {
                    a[j & 3] = fmaxf(a[j & 3], fmaxf(sacc[4 * j], sacc[4 * j + 1]));
                    b[j & 3] = fmaxf(b[j & 3], fmaxf(sacc[4 * j + 2], sacc[4 * j + 3]));
                }
                x0 = fmaxf(fmaxf(a[0], a[1]), fmaxf(a[2], a[3]));
                x1 = fmaxf(fmaxf(b[0], b[1]), fmaxf(b[2], b[3]));
                x0 = fmaxf(x0, __shfl_xor_sync(0xffffffffu, x0, 1));
                x1 = fmaxf(x1, __shfl_xor_sync(0xffffffffu, x1, 1));
                x0 = fmaxf(x0, __shfl_xor_sync(0xffffffffu, x0, 2));
                x1 = fmaxf(x1, __shfl_xor_sync(0xffffffffu, x1, 2));
            };
            auto out_of_range = [&](bool first) {
                int a0 = __vimax3_s32(__float_as_int(sacc[0]), __float_as_int(sacc[1]), __float_as_int(sacc[4]));
                int a1 = __vimax3_s32(__float_as_int(sacc[5]), __float_as_int(sacc[8]), __float_as_int(sacc[9]));
                int b0 = __vimax3_s32(__float_as_int(sacc[2]), __float_as_int(sacc[3]), __float_as_int(sacc[6]));
                int b1 = __vimax3_s32(__float_as_int(sacc[7]), __float_as_int(sacc[10]), __float_as_int(sacc[11]));
#pragma unroll
                for (int j = 3; j < 15; j += 2) {
                    a0 = __vimax3_s32(a0, __float_as_int(sacc[4 * j]), __float_as_int(sacc[4 * j + 1]));
                    b0 = __vimax3_s32(b0, __float_as_int(sacc[4 * j + 2]), __float_as_int(sacc[4 * j + 3]));
                    a1 = __vimax3_s32(a1, __float_as_int(sacc[4 * j + 4]), __float_as_int(sacc[4 * j + 5]));
                    b1 = __vimax3_s32(b1, __float_as_int(sacc[4 * j + 6]), __float_as_int(sacc[4 * j + 7]));
                }
                a0 = __vimax3_s32(a0, a1, max(__float_as_int(sacc[60]), __float_as_int(sacc[61])));
                b0 = __vimax3_s32(b0, b1, max(__float_as_int(sacc[62]), __float_as_int(sacc[63])));
                const bool bad = max(a0, b0) > 0x42800000 || (first && min(a0, b0) < 0);
                return __any_sync(0xffffffffu, bad) != 0;
            };
            auto exp_part = [&](auto J0_, auto J1_, float& t0, float& t1, float& u0, float& u1) {
#pragma unroll
                for (int j = decltype(J0_)::value; j < decltype(J1_)::value; j++) {
                    sacc[4 * j] = ex2(sacc[4 * j]); sacc[4 * j + 1] = ex2(sacc[4 * j + 1]);
                    sacc[4 * j + 2] = ex2(sacc[4 * j + 2]); sacc[4 * j + 3] = ex2(sacc[4 * j + 3]);
                    t0 += sacc[4 * j]; u0 += sacc[4 * j + 1];
                    t1 += sacc[4 * j + 2]; u1 += sacc[4 * j + 3];
                }
            };
            auto o_epilogue = [&](int hi, float a, float b) {
                store_tile128(g_oq + (size_t)row0 * (NH * DH) + (4 * g + hi) * 128 + 8 * q4, (size_t)8 * NH * DH, oacc, a, b);
                mbar_arrive_warp(bars + (B_PUB + 1 + hi) * 8, lane == 0);
            };
#define A_SPLIT 10
            constexpr int SPLIT = A_SPLIT;
            if (wg == 1) named_arrive(1, 288);
#define PP_SYNC() named_sync(1 + wg, 288)
#define PP_ARRIVE() named_arrive(2 - wg, 288)
            const int sg0 = 10 * ntiles;
            uint32_t ka = desc_lo(sbase + OFF_RINGG + (sg0 & 3) * SLOT, 16);
            uint32_t kr = B_EMPTYA + NP;
#pragma unroll
            for (int i = 0; i < 64; i++) { asm volatile("" : "=f"(oacc[i])); asm volatile("" : "=f"(sacc[i])); }
#pragma unroll
            for (int i = 0; i < 32; i++) asm volatile("" : "=r"(pf[i]));
#pragma unroll 1
            for (int it = 0; it < 16; it++) {
                const int j = it & 3;
                PP_SYNC();
                issue_qk(ka, ka + (SLOT >> 4));
                const uint32_t kc = kr;
                const int va = sa;
                if (it > 0) adv();
                if (it == 0) {
                    ka = desc_lo(sbase + OFF_RINGG + ((sg0 + 2) & 3) * SLOT, 16); kr = B_EMPTYA + NP + 1;
                } else if (it < 15) {
                    ka = desc_lo(sbase + sa * 2 * SLOT, 16); kr = B_EMPTYA + sa;
                    adv();
                }
                if (j == 1 && it > 1) o_epilogue((it >> 2) - 1, pl0, pl1);
                const __nv_bfloat16* qsrc = g_oq + (size_t)row0 * (NH * DH) + (4 * g + (it >> 2) + 1) * 128 + 8 * q4;
                if (j == 2 && it < 14) {
                    asm volatile("prefetch.global.L1 [%0];" :: "l"(qsrc));
                    asm volatile("prefetch.global.L1 [%0];" :: "l"(qsrc + 64));
                    asm volatile("prefetch.global.L1 [%0];" :: "l"(qsrc + (size_t)8 * NH * DH));
                    asm volatile("prefetch.global.L1 [%0];" :: "l"(qsrc + (size_t)8 * NH * DH + 64));
                }
                if (it > 0) issue_pv(sbase + va * 2 * SLOT, sbase + (va * 2 + 1) * SLOT, j != 1);
                else wgmma_commit();
                PP_ARRIVE();
                wgmma_wait<1>();
                fence_regs(sacc);
                float t0 = 0.f, t1 = 0.f, u0 = 0.f, u1 = 0.f;
                {
                    rel(kc);
                    if (j == 3 && it < 15) {
#pragma unroll
                        for (int m = 0; m < 4; m++) {
                            uint4 u0 = *reinterpret_cast<const uint4*>(qsrc + 32 * m);
                            uint4 u1 = *reinterpret_cast<const uint4*>(qsrc + (size_t)8 * NH * DH + 32 * m);
                            qf[8 * m + 0] = u0.x; qf[8 * m + 1] = u0.y; qf[8 * m + 2] = u0.z; qf[8 * m + 3] = u0.w;
                            qf[8 * m + 4] = u1.x; qf[8 * m + 5] = u1.y; qf[8 * m + 6] = u1.z; qf[8 * m + 7] = u1.w;
                        }
                    }
                    if (j == 0) { l0 = 0.f; l1 = 0.f; m0 = 0.f; m1 = 0.f; gen = false; }
                    if (!gen) gen = out_of_range(j == 0);
                    if (gen) {
                        float x0, x1;
                        rowmax(x0, x1);
                        if (j != 0) {
                            x0 = fmaxf(x0, m0); x1 = fmaxf(x1, m1);
                            sc0 = ex2(m0 - x0); sc1 = ex2(m1 - x1);
                            l0 *= sc0; l1 *= sc1;
                        }
                        m0 = x0; m1 = x1;
#pragma unroll
                        for (int jj = 0; jj < 16; jj++) {
                            sacc[4 * jj] -= m0; sacc[4 * jj + 1] -= m0;
                            sacc[4 * jj + 2] -= m1; sacc[4 * jj + 3] -= m1;
                        }
                    }
                    exp_part(IC<0>{}, IC<SPLIT>{}, t0, t1, u0, u1);
                }
                asm volatile("st.shared.f32 [%0], %1;" :: "r"(bars + 512), "f"((t0 + u0) + (t1 + u1)) : "memory");
                wgmma_wait<0>();
                fence_regs(oacc);
                fence_regs(pf);
                if (it > 0) rel(B_EMPTYA + va);
                {
                    exp_part(IC<SPLIT>{}, IC<16>{}, t0, t1, u0, u1);
                    l0 += t0 + u0; l1 += t1 + u1;
#pragma unroll
                    for (int jj = 0; jj < 16; jj++) {
                        pf[2 * jj] = pack_bf16(sacc[4 * jj], sacc[4 * jj + 1]);
                        pf[2 * jj + 1] = pack_bf16(sacc[4 * jj + 2], sacc[4 * jj + 3]);
                    }
                    if (j != 0 && gen) {
#pragma unroll
                        for (int jj = 0; jj < 16; jj++) {
                            oacc[4 * jj] *= sc0; oacc[4 * jj + 1] *= sc0;
                            oacc[4 * jj + 2] *= sc1; oacc[4 * jj + 3] *= sc1;
                        }
                    }
                    if (j == 3) {
                        float a = l0, b = l1;
                        a += __shfl_xor_sync(0xffffffffu, a, 1); b += __shfl_xor_sync(0xffffffffu, b, 1);
                        a += __shfl_xor_sync(0xffffffffu, a, 2); b += __shfl_xor_sync(0xffffffffu, b, 2);
                        pl0 = rcp(a); pl1 = rcp(b);
                    }
                }
            }
            {
                PP_SYNC();
                issue_pv(sbase + (NP - 1) * 2 * SLOT, sbase + ((NP - 1) * 2 + 1) * SLOT, 1);
                if (wg == 0) named_arrive(2, 288);
                wgmma_wait<0>();
                fence_regs(oacc);
                rel(B_EMPTYA + NP - 1);
            }
            o_epilogue(3, pl0, pl1);
        }

        {
            float a192[96], a128[64];
            constexpr int LAST = 4;
#pragma unroll 1
            for (int i = 0; i < nblk - LAST; i++) {
                const int st = i & 3;
                mbar_wait_u(bars + (B_FULL3 + st) * 8, (i >> 2) & 1);
                const uint32_t base = sbase + ((st + 3) & 3) * ST3;
                const uint32_t da = desc_lo(base + wg * 8192, 16);
                const uint32_t db = desc_lo(base + SLOT, 4096);
                wgmma_fence();
#pragma unroll
                for (int kk = 0; kk < 4; kk++) {
                    const uint32_t bb = db + (kk >> 1) * (20480 >> 4) + (kk & 1) * (2048 >> 4);
                    wgmma_ss_n192_tb(a192, da + kk * 2, bb, (i | kk) != 0);
                    wgmma_ss_n128_tb(a128, da + kk * 2, bb + ((3 * 4096) >> 4), (i | kk) != 0);
                }
                wgmma_commit();
                if (i > 0) {
                    wgmma_wait<1>();
                    mbar_arrive_remote_if(rbars + (B_EMPTY3 + ((i - 1) & 3)) * 8, el);
                }
            }
#pragma unroll
            for (int l = 0; l < LAST; l++) {
                const int i = nblk - LAST + l, st = i & 3;
                mbar_wait_u(bars + (B_FULL3 + st) * 8, (i >> 2) & 1);
                const uint32_t base = sbase + ((st + 3) & 3) * ST3;
                const uint32_t da = desc_lo(base + wg * 8192, 16);
                const uint32_t db = desc_lo(base + SLOT, 4096);
                wgmma_fence();
#pragma unroll
                for (int kk = 0; kk < 4; kk++)
                    wgmma_ss_n192_tb(a192, da + kk * 2, db + (kk >> 1) * (20480 >> 4) + (kk & 1) * (2048 >> 4), 1);
                wgmma_commit();
                if (l == 0) {
                    wgmma_wait<1>();
                    mbar_arrive_remote_if(rbars + (B_EMPTY3 + ((i - 1) & 3)) * 8, el);
                }
            }
            wgmma_fence();
#pragma unroll
            for (int l = 0; l < LAST; l++) {
                const int st = (nblk - LAST + l) & 3;
                const uint32_t base = sbase + ((st + 3) & 3) * ST3;
                const uint32_t da = desc_lo(base + wg * 8192, 16);
                const uint32_t db = desc_lo(base + SLOT, 4096) + ((3 * 4096) >> 4);
#pragma unroll
                for (int kk = 0; kk < 4; kk++)
                    wgmma_ss_n128_tb(a128, da + kk * 2, db + (kk >> 1) * (20480 >> 4) + (kk & 1) * (2048 >> 4), 1);
            }
            wgmma_commit();

            const int kq = g >> 1;
            uint4* const part = g_part + (size_t)((t * 2 + (g & 1)) * 4 + kq) * 4 * (PSLAB / 16) + tid;
            auto pack_slab = [&](auto S_, uint4 (&w)[5]) {
                constexpr int sl = decltype(S_)::value;
                static_for<0, 5>([&](auto I_) {
                    constexpr int i = decltype(I_)::value;
                    constexpr int jn = sl * 10 + 2 * i;
                    auto pk = [&](auto J_, int h) {
                        constexpr int j = decltype(J_)::value;
                        if constexpr (j < 24) return pack_bf16(a192[4 * j + h], a192[4 * j + h + 1]);
                        else return pack_bf16(a128[4 * (j - 24) + h], a128[4 * (j - 24) + h + 1]);
                    };
                    w[i] = make_uint4(pk(IC<jn>{}, 0), pk(IC<jn>{}, 2), pk(IC<jn + 1>{}, 0), pk(IC<jn + 1>{}, 2));
                });
            };
            wgmma_wait<1>();
            fence_regs(a192);
            static_for<0, 2>([&](auto S_) {
                constexpr int sl = decltype(S_)::value;
                if (sl != kq) {
                    uint4 w[5];
                    pack_slab(S_, w);
#pragma unroll
                    for (int i = 0; i < 5; i++) __stcg(part + sl * (PSLAB / 16) + i * 256, w[i]);
                }
            });
            wgmma_wait<0>();
            fence_regs(a128);
#pragma unroll
            for (int l = 0; l < LAST; l++) mbar_arrive_remote_if(rbars + (B_EMPTY3 + ((nblk - LAST + l) & 3)) * 8, el);
            static_for<2, 4>([&](auto S_) {
                constexpr int sl = decltype(S_)::value;
                if (sl != kq) {
                    uint4 w[5];
                    pack_slab(S_, w);
#pragma unroll
                    for (int i = 0; i < 5; i++) __stcg(part + sl * (PSLAB / 16) + i * 256, w[i]);
                }
            });
            mbar_arrive_warp(bars + (B_PUB + 5) * 8, lane == 0);
            named_sync(5, 256);
            static_for<0, 4>([&](auto S_) {
                constexpr int sl = decltype(S_)::value;
                if (sl == kq) {
                    uint4 w[5];
                    pack_slab(S_, w);
#pragma unroll
                    for (int i = 0; i < 5; i++)
                        asm volatile("st.shared.v4.b32 [%0], {%1, %2, %3, %4};"
                                     :: "r"(sbase + kq * PSLAB + (i * 256 + tid) * 16), "r"(w[i].x), "r"(w[i].y), "r"(w[i].z), "r"(w[i].w) : "memory");
                }
            });
            auto src_addr = [&](int src) { return sbase + (src == kq ? kq : 4 + (src < kq ? src : src - 1)) * PSLAB + tid * 16; };
            auto src_bar = [&](int src) { return bars + (B_IN + (src < kq ? src : src - 1)) * 8; };
            if (kq != 3) mbar_wait_u(src_bar(3), 0);
            {
                const uint32_t ga = src_addr(3);
#pragma unroll 1
                for (int i = 0; i < 5; i++) {
                    uint32_t w[4];
                    asm volatile("ld.shared.v4.b32 {%0, %1, %2, %3}, [%4];" : "=r"(w[0]), "=r"(w[1]), "=r"(w[2]), "=r"(w[3]) : "r"(ga + i * 4096) : "memory");
#pragma unroll
                    for (int e = 0; e < 4; e++) {
                        const float r2 = (e & 1) ? rs1 * rs1 : rs0 * rs0;
                        const uint32_t gb = pack_bf16(bf_lo(w[e]) * r2, bf_hi(w[e]) * r2);
                        w[e] = pack_bf16(silu_f(bf_lo(gb)), silu_f(bf_hi(gb)));
                    }
                    asm volatile("st.shared.v4.b32 [%0], {%1, %2, %3, %4};" :: "r"(ga + i * 4096), "r"(w[0]), "r"(w[1]), "r"(w[2]), "r"(w[3]) : "memory");
                }
            }
            {
                const uint32_t ga = src_addr(3);
                const uint32_t xs = sbase + XS_OFF + (wg * 64 + wl * 16 + (lane >> 2)) * 80 + q4 * 4;
                const uint32_t os = sbase + XS_OFF + PSLAB + (wg * 64 + wl * 16 + (lane >> 2)) * 160 + q4 * 4;
                auto xaddr = [&](int i) { const int jn = 2 * (i >> 2) + ((i >> 1) & 1); return xs + (jn / 5) * (PSLAB / 2) + (i & 1) * 8 * 80 + (jn % 5) * 16; };
                uint32_t p0[20], p1[20], p2[20], a[20], x[20];
                mbar_wait_u(bars + B_XS * 8, 0);
#pragma unroll
                for (int i = 0; i < 5; i++)
                    asm volatile("ld.shared.v4.b32 {%0, %1, %2, %3}, [%4];" : "=r"(a[4 * i]), "=r"(a[4 * i + 1]), "=r"(a[4 * i + 2]), "=r"(a[4 * i + 3]) : "r"(ga + i * 4096) : "memory");
#pragma unroll
                for (int i = 0; i < 20; i++) asm volatile("ld.shared.b32 %0, [%1];" : "=r"(x[i]) : "r"(xaddr(i)) : "memory");
#pragma unroll 1
                for (int v = 0; v < 3; v++) if (v != kq) mbar_wait_u(src_bar(v), 0);
                {
                    const uint4* mail = g_part + (size_t)((t * 2 + (g & 1)) * 4 * 4 + kq) * (PSLAB / 16) + tid;
                    auto fetch = [&](int v, uint32_t (&p)[20]) {
                        if (v == kq) {
#pragma unroll
                            for (int i = 0; i < 5; i++)
                                asm volatile("ld.shared.v4.b32 {%0, %1, %2, %3}, [%4];" : "=r"(p[4 * i]), "=r"(p[4 * i + 1]), "=r"(p[4 * i + 2]), "=r"(p[4 * i + 3])
                                             : "r"(sbase + kq * PSLAB + tid * 16 + i * 4096) : "memory");
                        } else {
#pragma unroll
                            for (int i = 0; i < 5; i++) {
                                const uint4 u = __ldcg(mail + (size_t)v * 4 * (PSLAB / 16) + i * 256);
                                p[4 * i] = u.x; p[4 * i + 1] = u.y; p[4 * i + 2] = u.z; p[4 * i + 3] = u.w;
                            }
                        }
                    };
                    fetch(0, p0); fetch(1, p1); fetch(2, p2);
                }
#pragma unroll
                for (int i = 0; i < 20; i++) {
                    const uint32_t sb = pack_bf16(bf_lo(p0[i]) + bf_lo(p1[i]) + bf_lo(p2[i]), bf_hi(p0[i]) + bf_hi(p1[i]) + bf_hi(p2[i]));
                    const uint32_t r = hmul2_bf16(sb, a[i]);
                    const uint32_t o = pack_bf16(bf_lo(x[i]) + bf_lo(r), bf_hi(x[i]) + bf_hi(r));
                    asm volatile("st.shared.b32 [%0], %1;" :: "r"(os + (i & 1) * 8 * 160 + (2 * (i >> 2) + ((i >> 1) & 1)) * 16), "r"(o) : "memory");
                }
            }
            asm volatile("fence.proxy.async.shared::cta;" ::: "memory");
            named_sync(5, 256);
            if (tid == 0) {
                asm volatile("cp.async.bulk.tensor.2d.global.shared::cta.bulk_group [%0, {%2, %3}], [%1];"
                             :: "l"(&tm_out), "r"(sbase + XS_OFF + PSLAB), "r"((g & 1) * 320 + kq * 80), "r"(t * 128) : "memory");
                asm volatile("cp.async.bulk.commit_group;" ::: "memory");
                asm volatile("cp.async.bulk.wait_group.read 0;" ::: "memory");
            }
        }
    }
}

typedef CUresult (*PFN_encodeTiled)(CUtensorMap*, CUtensorMapDataType, cuuint32_t, void*, const cuuint64_t*, const cuuint64_t*,
                                    const cuuint32_t*, const cuuint32_t*, CUtensorMapInterleave, CUtensorMapSwizzle,
                                    CUtensorMapL2promotion, CUtensorMapFloatOOBfill);

bool encode(PFN_encodeTiled fn, CUtensorMap* m, const void* base, int rank, const cuuint64_t* dims, const cuuint64_t* strides,
            const cuuint32_t* box) {
    cuuint32_t es[5] = {1, 1, 1, 1, 1};
    return fn(m, CU_TENSOR_MAP_DATA_TYPE_BFLOAT16, rank, const_cast<void*>(base), dims, strides, box, es,
              CU_TENSOR_MAP_INTERLEAVE_NONE, CU_TENSOR_MAP_SWIZZLE_128B, CU_TENSOR_MAP_L2_PROMOTION_L2_256B,
              CU_TENSOR_MAP_FLOAT_OOB_FILL_NONE) == CUDA_SUCCESS;
}
bool encode2d(PFN_encodeTiled fn, CUtensorMap* m, const void* base, uint64_t cols, uint64_t rows, uint32_t box_rows) {
    cuuint64_t dims[2] = {cols, rows};
    cuuint64_t strides[1] = {cols * 2};
    cuuint32_t box[2] = {64, box_rows};
    return encode(fn, m, base, 2, dims, strides, box);
}
bool encode_out(PFN_encodeTiled fn, CUtensorMap* m, void* base, uint32_t box_cols) {
    cuuint64_t dims[2] = {DM, S_LEN};
    cuuint64_t strides[1] = {DM * 2};
    cuuint32_t box[2] = {box_cols, 128};
    cuuint32_t es[2] = {1, 1};
    return fn(m, CU_TENSOR_MAP_DATA_TYPE_BFLOAT16, 2, base, dims, strides, box, es, CU_TENSOR_MAP_INTERLEAVE_NONE,
              CU_TENSOR_MAP_SWIZZLE_NONE, CU_TENSOR_MAP_L2_PROMOTION_NONE, CU_TENSOR_MAP_FLOAT_OOB_FILL_NONE) == CUDA_SUCCESS;
}
bool encode_perm(PFN_encodeTiled fn, CUtensorMap* m, const void* base, uint64_t rows) {
    cuuint64_t dims[5] = {64, 2, rows / 8, 4, 10};
    cuuint64_t strides[4] = {DM * 2, 8 * DM * 2, 2 * DM * 2, 128};
    cuuint32_t box[5] = {64, 2, 4, 4, 5};
    return encode(fn, m, base, 5, dims, strides, box);
}

}

extern "C" void kernel_launch(void* const* d_in, const int* in_sizes, int n_in, void* d_out, int out_size) {
    (void)in_sizes; (void)n_in; (void)out_size;
    static PFN_encodeTiled enc = nullptr;
    static void* p_oq = nullptr;
    static void* p_h = nullptr;
    static int use_helpers = 0;
    if (!enc) {
        void* p = nullptr;
        cudaDriverEntryPointQueryResult qr;
        if (cudaGetDriverEntryPoint("cuTensorMapEncodeTiled", &p, cudaEnableDefault, &qr) != cudaSuccess || !p) {
            fprintf(stderr, "cuTensorMapEncodeTiled not found\n");
            return;
        }
        enc = (PFN_encodeTiled)p;
        cudaGetSymbolAddress(&p_oq, g_oq);
        cudaGetSymbolAddress(&p_h, g_h);
        cudaFuncSetAttribute(fused_kernel<0>, cudaFuncAttributeMaxDynamicSharedMemorySize, SMEM_BYTES);
        cudaFuncSetAttribute(fused_kernel<1>, cudaFuncAttributeMaxDynamicSharedMemorySize, SMEM_BYTES);
        cudaLaunchConfig_t q = {};
        q.gridDim = dim3(132); q.blockDim = dim3(384); q.dynamicSmemBytes = SMEM_BYTES;
        cudaLaunchAttribute qa[1];
        qa[0].id = cudaLaunchAttributeClusterDimension;
        qa[0].val.clusterDim.x = 2; qa[0].val.clusterDim.y = 1; qa[0].val.clusterDim.z = 1;
        q.attrs = qa; q.numAttrs = 1;
        int nc = 0;
        if (cudaOccupancyMaxActiveClusters(&nc, fused_kernel<1>, &q) != cudaSuccess) { nc = 0; (void)cudaGetLastError(); }
        use_helpers = nc >= 66 ? 1 : 0;
    }
    const void* x = d_in[0];
    const void* kc = d_in[1];
    const void* vc = d_in[2];
    const void* wq = d_in[3];
    const void* wo = d_in[4];
    const void* w1 = d_in[6];
    const void* w3 = d_in[7];
    const void* w2 = d_in[8];
    CUtensorMap tm_w1, tm_w3, tm_wq, tm_k, tm_v, tm_wo, tm_w2, tm_o, tm_h, tm_x, tm_out, tm_xs;
    bool ok = encode2d(enc, &tm_w1, w1, FF, DM, 64) && encode2d(enc, &tm_w3, w3, FF, DM, 64) &&
              encode2d(enc, &tm_wq, wq, NH * DH, DM, 64) && encode2d(enc, &tm_k, kc, DH, (uint64_t)NH * SKV, 64) &&
              encode2d(enc, &tm_v, vc, DH, (uint64_t)NH * SKV, 64) && encode_perm(enc, &tm_wo, wo, NH * DH) &&
              encode_perm(enc, &tm_w2, w2, FF) && encode2d(enc, &tm_o, p_oq, NH * DH, S_LEN, 128) &&
              encode2d(enc, &tm_h, p_h, FF, S_LEN, 128) && encode2d(enc, &tm_x, x, DM, S_LEN, 128) && encode_out(enc, &tm_out, d_out, 80) && encode_out(enc, &tm_xs, const_cast<void*>(x), 40);
    if (!ok) { fprintf(stderr, "tensor map encode failed\n"); return; }
    cudaLaunchConfig_t cfg = {};
    cfg.gridDim = dim3(use_helpers ? 132 : 128);
    cfg.blockDim = dim3(384);
    cfg.dynamicSmemBytes = SMEM_BYTES;
    cfg.stream = cudaStreamPerThread;
    cudaLaunchAttribute at[1];
    at[0].id = cudaLaunchAttributeClusterDimension;
    at[0].val.clusterDim.x = 2; at[0].val.clusterDim.y = 1; at[0].val.clusterDim.z = 1;
    cfg.attrs = at;
    cfg.numAttrs = 1;
    cudaError_t e = cudaLaunchKernelEx(&cfg, use_helpers ? fused_kernel<1> : fused_kernel<0>, tm_w1, tm_w3, tm_wq, tm_k, tm_v, tm_wo, tm_w2, tm_o, tm_h, tm_x, tm_out, tm_xs);
    if (e != cudaSuccess) fprintf(stderr, "launch failed: %s\n", cudaGetErrorString(e));
}
```
